```python
import torch

def _softmax(x, axis=-1):
    return torch.softmax(x, dim=axis)
def _gelu(x):
    return torch.nn.functional.gelu(x, approximate="tanh")
def _silu(x):
    return torch.nn.functional.silu(x)
def _sigmoid(x):
    return torch.sigmoid(x)
def _layernorm(x, axis=-1, eps=1e-5):
    m = x.mean(dim=axis, keepdim=True)
    v = x.var(dim=axis, keepdim=True, unbiased=False)
    return (x - m) / torch.sqrt(v + eps)
def _scatter_add(tgt, idx, src, axis=0):
    return tgt.clone().index_add_(axis, idx, src)
def _segment_sum(src, seg, n):
    out = torch.zeros((n,) + src.shape[1:], dtype=src.dtype)
    return out.index_add_(0, seg, src)
def _pad(x, pw):
    flat = tuple(v for pair in reversed(pw) for v in pair)
    return torch.nn.functional.pad(x, flat)

kernel_name = 'sequential_preLN__softmax_full_mha__dense_activation_squared_relu__prompt'

def setup_inputs():

    _w = (lambda a: (lambda t: t.to(torch.bfloat16) if t.is_floating_point() else t)(torch.as_tensor(a)))
    def _A_setup():
        B, S, D = 1, 2048, 640
        return {
            "x": _w((lambda *s: torch.randn(*s, dtype=torch.bfloat16) * 0.05)(B, S, D)),
            "wqkv": _w((lambda *s: torch.randn(*s, dtype=torch.bfloat16) * 0.05)(D, 3 * D)),
            "wo": _w((lambda *s: torch.randn(*s, dtype=torch.bfloat16) * 0.05)(D, D)),
        }
    _A_in = _A_setup()

    def _B_setup():
        B, S, D, F = 1, 2048, 640, 1536
        return {
            "x": _w((lambda *s: torch.randn(*s, dtype=torch.bfloat16) * 0.05)(B, S, D)),
            "w1": _w((lambda *s: torch.randn(*s, dtype=torch.bfloat16) * 0.05)(D, F)),
            "b1": _w((lambda *s: torch.randn(*s, dtype=torch.bfloat16) * 0.8)(F)),
            "w2": _w((lambda *s: torch.randn(*s, dtype=torch.bfloat16) * 0.05)(F, D)),
            "b2": _w((lambda *s: torch.randn(*s, dtype=torch.bfloat16) * 3.2)(D)),
        }
    _B_in = _B_setup()

    return {
        "A_x": _A_in["x"],
        "A_wqkv": _A_in["wqkv"],
        "A_wo": _A_in["wo"],
        "B_x": _B_in["x"],
        "B_w1": _B_in["w1"],
        "B_b1": _B_in["b1"],
        "B_w2": _B_in["w2"],
        "B_b2": _B_in["b2"],
    }

def reference(A_x, A_wqkv, A_wo, B_x, B_w1, B_b1, B_w2, B_b2):
    def _A_ref(x, wqkv, wo):
        B, S, D = x.shape
        H = 32; Dh = D // H
        qkv = (lambda x, *d: x.permute(*d))((x @ wqkv).reshape(B, S, 3, H, Dh), 2, 0, 3, 1, 4)
        q, k, v = qkv[0], qkv[1], qkv[2]
        scale = Dh ** -0.5
        scores = torch.einsum("bhqd,bhkd->bhqk", q, k) * scale
        p = _softmax(scores, axis=-1)
        o = torch.einsum("bhqk,bhkd->bhqd", p, v)
        return (lambda x, *d: x.permute(*d))(o, 0, 2, 1, 3).reshape(B, S, D) @ wo

    def _B_ref(x, w1, b1, w2, b2):
        h = torch.einsum("bsd,df->bsf", x, w1) + b1
        zero = torch.zeros_like(h)
        r = torch.where(h > zero, h, zero)
        h = r * r
        out = torch.einsum("bsf,fd->bsd", h, w2) + b2
        return out

    x = A_x
    h = x + _A_ref(_layernorm(x, axis=-1), A_wqkv, A_wo)
    h2 = h + _B_ref(_layernorm(h, axis=-1), B_w1, B_b1, B_w2, B_b2)
    return h2
```

```cpp
#include <cuda_runtime.h>
#include <cuda_bf16.h>
#include <cuda.h>
#include <stdint.h>

namespace {

constexpr int SEQ = 2048, DM = 640, FF = 1536, NH = 32;
constexpr int CHUNK = 6144;
constexpr int WDL = 800, XDL = 500;
constexpr int INIT = 2, LPI = 4, NBAR = 5;
constexpr int RTU = 4;
constexpr int STL = 2, XS = 5;
constexpr int HLD = 5, HAR = 7;
constexpr uint32_t MUFU_MASK = 0x2921;
constexpr float M_LIMIT = 48.f;
constexpr int HBLK = 10240;

constexpr int PAIR = 32768;
__device__ __align__(1024) uint8_t g_qkv[NH / 2 * 16 * PAIR];
__device__ __align__(1024) uint8_t g_o[32 * 80 * 1024];
__device__ __align__(1024) uint8_t g_h[32 * 8 * HBLK];
__device__ __align__(1024) uint8_t g_hid[32 * 192 * 1024];
__device__ __align__(1024) uint8_t g_wo[8 * 80 * 1280];
__device__ __align__(1024) uint8_t g_w1[8 * 80 * 3072];
__device__ __align__(1024) uint8_t g_w2[8 * 192 * 1280];
__device__ __align__(16) float g_kpart[NH * 128];
__device__ __align__(16) float2 g_stat1[SEQ];
__device__ __align__(16) float2 g_stat2[16 * 8 * 128];
__device__ __align__(16) float g_csq[16 * 3 * DM];
__device__ __align__(16) float g_cs1[FF];
__device__ __align__(128) unsigned g_flag[32 * 32];
#define STAMP(k, i)

template<int TB, uint32_t HB> __device__ __forceinline__ void wgmma_rs_n24(float (&d)[12], const uint32_t (&a)[4], uint32_t db) {
  asm volatile("{.reg .b64 db; mov.b64 db, {%16, %18};\nwgmma.mma_async.sync.aligned.m64n24k16.f32.bf16.bf16 "
    "{%0,%1,%2,%3,%4,%5,%6,%7,%8,%9,%10,%11}, {%12,%13,%14,%15}, db, 1, 1, 1, %17;}"
    : "+f"(d[0]),"+f"(d[1]),"+f"(d[2]),"+f"(d[3]),"+f"(d[4]),"+f"(d[5]),"+f"(d[6]),"+f"(d[7]),"+f"(d[8]),"+f"(d[9]),"+f"(d[10]),"+f"(d[11])
    : "r"(a[0]),"r"(a[1]),"r"(a[2]),"r"(a[3]), "r"(db), "n"(TB), "n"(HB));
}
template<int TB, uint32_t HB> __device__ __forceinline__ void wgmma_rs_n64(float (&d)[32], const uint32_t (&a)[4], uint32_t db) {
  asm volatile("{.reg .b64 db; mov.b64 db, {%36, %38};\nwgmma.mma_async.sync.aligned.m64n64k16.f32.bf16.bf16 "
    "{%0,%1,%2,%3,%4,%5,%6,%7,%8,%9,%10,%11,%12,%13,%14,%15,%16,%17,%18,%19,%20,%21,%22,%23,%24,%25,%26,%27,%28,%29,%30,%31}, {%32,%33,%34,%35}, db, 1, 1, 1, %37;}"
    : "+f"(d[0]),"+f"(d[1]),"+f"(d[2]),"+f"(d[3]),"+f"(d[4]),"+f"(d[5]),"+f"(d[6]),"+f"(d[7]),"+f"(d[8]),"+f"(d[9]),"+f"(d[10]),"+f"(d[11]),"+f"(d[12]),"+f"(d[13]),"+f"(d[14]),"+f"(d[15]),"+f"(d[16]),"+f"(d[17]),"+f"(d[18]),"+f"(d[19]),"+f"(d[20]),"+f"(d[21]),"+f"(d[22]),"+f"(d[23]),"+f"(d[24]),"+f"(d[25]),"+f"(d[26]),"+f"(d[27]),"+f"(d[28]),"+f"(d[29]),"+f"(d[30]),"+f"(d[31])
    : "r"(a[0]),"r"(a[1]),"r"(a[2]),"r"(a[3]), "r"(db), "n"(TB), "n"(HB));
}
template<int TB, uint32_t HB> __device__ __forceinline__ void wgmma_rs_n64_z(float (&d)[32], const uint32_t (&a)[4], uint32_t db) {
  asm volatile("{.reg .b64 db; mov.b64 db, {%36, %38};\nwgmma.mma_async.sync.aligned.m64n64k16.f32.bf16.bf16 "
    "{%0,%1,%2,%3,%4,%5,%6,%7,%8,%9,%10,%11,%12,%13,%14,%15,%16,%17,%18,%19,%20,%21,%22,%23,%24,%25,%26,%27,%28,%29,%30,%31}, {%32,%33,%34,%35}, db, 0, 1, 1, %37;}"
    : "=f"(d[0]),"=f"(d[1]),"=f"(d[2]),"=f"(d[3]),"=f"(d[4]),"=f"(d[5]),"=f"(d[6]),"=f"(d[7]),"=f"(d[8]),"=f"(d[9]),"=f"(d[10]),"=f"(d[11]),"=f"(d[12]),"=f"(d[13]),"=f"(d[14]),"=f"(d[15]),"=f"(d[16]),"=f"(d[17]),"=f"(d[18]),"=f"(d[19]),"=f"(d[20]),"=f"(d[21]),"=f"(d[22]),"=f"(d[23]),"=f"(d[24]),"=f"(d[25]),"=f"(d[26]),"=f"(d[27]),"=f"(d[28]),"=f"(d[29]),"=f"(d[30]),"=f"(d[31])
    : "r"(a[0]),"r"(a[1]),"r"(a[2]),"r"(a[3]), "r"(db), "n"(TB), "n"(HB));
}
template<int TB, uint32_t HB> __device__ __forceinline__ void wgmma_rs_n80(float (&d)[40], const uint32_t (&a)[4], uint32_t db) {
  asm volatile("{.reg .b64 db; mov.b64 db, {%44, %46};\nwgmma.mma_async.sync.aligned.m64n80k16.f32.bf16.bf16 "
    "{%0,%1,%2,%3,%4,%5,%6,%7,%8,%9,%10,%11,%12,%13,%14,%15,%16,%17,%18,%19,%20,%21,%22,%23,%24,%25,%26,%27,%28,%29,%30,%31,%32,%33,%34,%35,%36,%37,%38,%39}, {%40,%41,%42,%43}, db, 1, 1, 1, %45;}"
    : "+f"(d[0]),"+f"(d[1]),"+f"(d[2]),"+f"(d[3]),"+f"(d[4]),"+f"(d[5]),"+f"(d[6]),"+f"(d[7]),"+f"(d[8]),"+f"(d[9]),"+f"(d[10]),"+f"(d[11]),"+f"(d[12]),"+f"(d[13]),"+f"(d[14]),"+f"(d[15]),"+f"(d[16]),"+f"(d[17]),"+f"(d[18]),"+f"(d[19]),"+f"(d[20]),"+f"(d[21]),"+f"(d[22]),"+f"(d[23]),"+f"(d[24]),"+f"(d[25]),"+f"(d[26]),"+f"(d[27]),"+f"(d[28]),"+f"(d[29]),"+f"(d[30]),"+f"(d[31]),"+f"(d[32]),"+f"(d[33]),"+f"(d[34]),"+f"(d[35]),"+f"(d[36]),"+f"(d[37]),"+f"(d[38]),"+f"(d[39])
    : "r"(a[0]),"r"(a[1]),"r"(a[2]),"r"(a[3]), "r"(db), "n"(TB), "n"(HB));
}
template<int TB, uint32_t HB> __device__ __forceinline__ void wgmma_rs_n80_z(float (&d)[40], const uint32_t (&a)[4], uint32_t db) {
  asm volatile("{.reg .b64 db; mov.b64 db, {%44, %46};\nwgmma.mma_async.sync.aligned.m64n80k16.f32.bf16.bf16 "
    "{%0,%1,%2,%3,%4,%5,%6,%7,%8,%9,%10,%11,%12,%13,%14,%15,%16,%17,%18,%19,%20,%21,%22,%23,%24,%25,%26,%27,%28,%29,%30,%31,%32,%33,%34,%35,%36,%37,%38,%39}, {%40,%41,%42,%43}, db, 0, 1, 1, %45;}"
    : "=f"(d[0]),"=f"(d[1]),"=f"(d[2]),"=f"(d[3]),"=f"(d[4]),"=f"(d[5]),"=f"(d[6]),"=f"(d[7]),"=f"(d[8]),"=f"(d[9]),"=f"(d[10]),"=f"(d[11]),"=f"(d[12]),"=f"(d[13]),"=f"(d[14]),"=f"(d[15]),"=f"(d[16]),"=f"(d[17]),"=f"(d[18]),"=f"(d[19]),"=f"(d[20]),"=f"(d[21]),"=f"(d[22]),"=f"(d[23]),"=f"(d[24]),"=f"(d[25]),"=f"(d[26]),"=f"(d[27]),"=f"(d[28]),"=f"(d[29]),"=f"(d[30]),"=f"(d[31]),"=f"(d[32]),"=f"(d[33]),"=f"(d[34]),"=f"(d[35]),"=f"(d[36]),"=f"(d[37]),"=f"(d[38]),"=f"(d[39])
    : "r"(a[0]),"r"(a[1]),"r"(a[2]),"r"(a[3]), "r"(db), "n"(TB), "n"(HB));
}
template<int TB, uint32_t HB> __device__ __forceinline__ void wgmma_rs_n192(float (&d)[96], const uint32_t (&a)[4], uint32_t db) {
  asm volatile("{.reg .b64 db; mov.b64 db, {%100, %102};\nwgmma.mma_async.sync.aligned.m64n192k16.f32.bf16.bf16 "
    "{%0,%1,%2,%3,%4,%5,%6,%7,%8,%9,%10,%11,%12,%13,%14,%15,%16,%17,%18,%19,%20,%21,%22,%23,%24,%25,%26,%27,%28,%29,%30,%31,%32,%33,%34,%35,%36,%37,%38,%39,%40,%41,%42,%43,%44,%45,%46,%47,%48,%49,%50,%51,%52,%53,%54,%55,%56,%57,%58,%59,%60,%61,%62,%63,%64,%65,%66,%67,%68,%69,%70,%71,%72,%73,%74,%75,%76,%77,%78,%79,%80,%81,%82,%83,%84,%85,%86,%87,%88,%89,%90,%91,%92,%93,%94,%95}, {%96,%97,%98,%99}, db, 1, 1, 1, %101;}"
    : "+f"(d[0]),"+f"(d[1]),"+f"(d[2]),"+f"(d[3]),"+f"(d[4]),"+f"(d[5]),"+f"(d[6]),"+f"(d[7]),"+f"(d[8]),"+f"(d[9]),"+f"(d[10]),"+f"(d[11]),"+f"(d[12]),"+f"(d[13]),"+f"(d[14]),"+f"(d[15]),"+f"(d[16]),"+f"(d[17]),"+f"(d[18]),"+f"(d[19]),"+f"(d[20]),"+f"(d[21]),"+f"(d[22]),"+f"(d[23]),"+f"(d[24]),"+f"(d[25]),"+f"(d[26]),"+f"(d[27]),"+f"(d[28]),"+f"(d[29]),"+f"(d[30]),"+f"(d[31]),"+f"(d[32]),"+f"(d[33]),"+f"(d[34]),"+f"(d[35]),"+f"(d[36]),"+f"(d[37]),"+f"(d[38]),"+f"(d[39]),"+f"(d[40]),"+f"(d[41]),"+f"(d[42]),"+f"(d[43]),"+f"(d[44]),"+f"(d[45]),"+f"(d[46]),"+f"(d[47]),"+f"(d[48]),"+f"(d[49]),"+f"(d[50]),"+f"(d[51]),"+f"(d[52]),"+f"(d[53]),"+f"(d[54]),"+f"(d[55]),"+f"(d[56]),"+f"(d[57]),"+f"(d[58]),"+f"(d[59]),"+f"(d[60]),"+f"(d[61]),"+f"(d[62]),"+f"(d[63]),"+f"(d[64]),"+f"(d[65]),"+f"(d[66]),"+f"(d[67]),"+f"(d[68]),"+f"(d[69]),"+f"(d[70]),"+f"(d[71]),"+f"(d[72]),"+f"(d[73]),"+f"(d[74]),"+f"(d[75]),"+f"(d[76]),"+f"(d[77]),"+f"(d[78]),"+f"(d[79]),"+f"(d[80]),"+f"(d[81]),"+f"(d[82]),"+f"(d[83]),"+f"(d[84]),"+f"(d[85]),"+f"(d[86]),"+f"(d[87]),"+f"(d[88]),"+f"(d[89]),"+f"(d[90]),"+f"(d[91]),"+f"(d[92]),"+f"(d[93]),"+f"(d[94]),"+f"(d[95])
    : "r"(a[0]),"r"(a[1]),"r"(a[2]),"r"(a[3]), "r"(db), "n"(TB), "n"(HB));
}
template<int TB, uint32_t HB> __device__ __forceinline__ void wgmma_rs_n192_z(float (&d)[96], const uint32_t (&a)[4], uint32_t db) {
  asm volatile("{.reg .b64 db; mov.b64 db, {%100, %102};\nwgmma.mma_async.sync.aligned.m64n192k16.f32.bf16.bf16 "
    "{%0,%1,%2,%3,%4,%5,%6,%7,%8,%9,%10,%11,%12,%13,%14,%15,%16,%17,%18,%19,%20,%21,%22,%23,%24,%25,%26,%27,%28,%29,%30,%31,%32,%33,%34,%35,%36,%37,%38,%39,%40,%41,%42,%43,%44,%45,%46,%47,%48,%49,%50,%51,%52,%53,%54,%55,%56,%57,%58,%59,%60,%61,%62,%63,%64,%65,%66,%67,%68,%69,%70,%71,%72,%73,%74,%75,%76,%77,%78,%79,%80,%81,%82,%83,%84,%85,%86,%87,%88,%89,%90,%91,%92,%93,%94,%95}, {%96,%97,%98,%99}, db, 0, 1, 1, %101;}"
    : "=f"(d[0]),"=f"(d[1]),"=f"(d[2]),"=f"(d[3]),"=f"(d[4]),"=f"(d[5]),"=f"(d[6]),"=f"(d[7]),"=f"(d[8]),"=f"(d[9]),"=f"(d[10]),"=f"(d[11]),"=f"(d[12]),"=f"(d[13]),"=f"(d[14]),"=f"(d[15]),"=f"(d[16]),"=f"(d[17]),"=f"(d[18]),"=f"(d[19]),"=f"(d[20]),"=f"(d[21]),"=f"(d[22]),"=f"(d[23]),"=f"(d[24]),"=f"(d[25]),"=f"(d[26]),"=f"(d[27]),"=f"(d[28]),"=f"(d[29]),"=f"(d[30]),"=f"(d[31]),"=f"(d[32]),"=f"(d[33]),"=f"(d[34]),"=f"(d[35]),"=f"(d[36]),"=f"(d[37]),"=f"(d[38]),"=f"(d[39]),"=f"(d[40]),"=f"(d[41]),"=f"(d[42]),"=f"(d[43]),"=f"(d[44]),"=f"(d[45]),"=f"(d[46]),"=f"(d[47]),"=f"(d[48]),"=f"(d[49]),"=f"(d[50]),"=f"(d[51]),"=f"(d[52]),"=f"(d[53]),"=f"(d[54]),"=f"(d[55]),"=f"(d[56]),"=f"(d[57]),"=f"(d[58]),"=f"(d[59]),"=f"(d[60]),"=f"(d[61]),"=f"(d[62]),"=f"(d[63]),"=f"(d[64]),"=f"(d[65]),"=f"(d[66]),"=f"(d[67]),"=f"(d[68]),"=f"(d[69]),"=f"(d[70]),"=f"(d[71]),"=f"(d[72]),"=f"(d[73]),"=f"(d[74]),"=f"(d[75]),"=f"(d[76]),"=f"(d[77]),"=f"(d[78]),"=f"(d[79]),"=f"(d[80]),"=f"(d[81]),"=f"(d[82]),"=f"(d[83]),"=f"(d[84]),"=f"(d[85]),"=f"(d[86]),"=f"(d[87]),"=f"(d[88]),"=f"(d[89]),"=f"(d[90]),"=f"(d[91]),"=f"(d[92]),"=f"(d[93]),"=f"(d[94]),"=f"(d[95])
    : "r"(a[0]),"r"(a[1]),"r"(a[2]),"r"(a[3]), "r"(db), "n"(TB), "n"(HB));
}
template<int TB, uint32_t HB> __device__ __forceinline__ void wgmma_ss_n80(float (&d)[40], uint32_t da, uint32_t db) {
  asm volatile("{.reg .b64 da, db; mov.b64 da, {%40, %43}; mov.b64 db, {%41, %43};\nwgmma.mma_async.sync.aligned.m64n80k16.f32.bf16.bf16 "
    "{%0,%1,%2,%3,%4,%5,%6,%7,%8,%9,%10,%11,%12,%13,%14,%15,%16,%17,%18,%19,%20,%21,%22,%23,%24,%25,%26,%27,%28,%29,%30,%31,%32,%33,%34,%35,%36,%37,%38,%39}, da, db, 1, 1, 1, 0, %42;}"
    : "+f"(d[0]),"+f"(d[1]),"+f"(d[2]),"+f"(d[3]),"+f"(d[4]),"+f"(d[5]),"+f"(d[6]),"+f"(d[7]),"+f"(d[8]),"+f"(d[9]),"+f"(d[10]),"+f"(d[11]),"+f"(d[12]),"+f"(d[13]),"+f"(d[14]),"+f"(d[15]),"+f"(d[16]),"+f"(d[17]),"+f"(d[18]),"+f"(d[19]),"+f"(d[20]),"+f"(d[21]),"+f"(d[22]),"+f"(d[23]),"+f"(d[24]),"+f"(d[25]),"+f"(d[26]),"+f"(d[27]),"+f"(d[28]),"+f"(d[29]),"+f"(d[30]),"+f"(d[31]),"+f"(d[32]),"+f"(d[33]),"+f"(d[34]),"+f"(d[35]),"+f"(d[36]),"+f"(d[37]),"+f"(d[38]),"+f"(d[39])
    : "r"(da), "r"(db), "n"(TB), "n"(HB));
}
template<int TB, uint32_t HB> __device__ __forceinline__ void wgmma_ss_n80_z(float (&d)[40], uint32_t da, uint32_t db) {
  asm volatile("{.reg .b64 da, db; mov.b64 da, {%40, %43}; mov.b64 db, {%41, %43};\nwgmma.mma_async.sync.aligned.m64n80k16.f32.bf16.bf16 "
    "{%0,%1,%2,%3,%4,%5,%6,%7,%8,%9,%10,%11,%12,%13,%14,%15,%16,%17,%18,%19,%20,%21,%22,%23,%24,%25,%26,%27,%28,%29,%30,%31,%32,%33,%34,%35,%36,%37,%38,%39}, da, db, 0, 1, 1, 0, %42;}"
    : "=f"(d[0]),"=f"(d[1]),"=f"(d[2]),"=f"(d[3]),"=f"(d[4]),"=f"(d[5]),"=f"(d[6]),"=f"(d[7]),"=f"(d[8]),"=f"(d[9]),"=f"(d[10]),"=f"(d[11]),"=f"(d[12]),"=f"(d[13]),"=f"(d[14]),"=f"(d[15]),"=f"(d[16]),"=f"(d[17]),"=f"(d[18]),"=f"(d[19]),"=f"(d[20]),"=f"(d[21]),"=f"(d[22]),"=f"(d[23]),"=f"(d[24]),"=f"(d[25]),"=f"(d[26]),"=f"(d[27]),"=f"(d[28]),"=f"(d[29]),"=f"(d[30]),"=f"(d[31]),"=f"(d[32]),"=f"(d[33]),"=f"(d[34]),"=f"(d[35]),"=f"(d[36]),"=f"(d[37]),"=f"(d[38]),"=f"(d[39])
    : "r"(da), "r"(db), "n"(TB), "n"(HB));
}
template<int TB, uint32_t HB> __device__ __forceinline__ void wgmma_ss_n192(float (&d)[96], uint32_t da, uint32_t db) {
  asm volatile("{.reg .b64 da, db; mov.b64 da, {%96, %99}; mov.b64 db, {%97, %99};\nwgmma.mma_async.sync.aligned.m64n192k16.f32.bf16.bf16 "
    "{%0,%1,%2,%3,%4,%5,%6,%7,%8,%9,%10,%11,%12,%13,%14,%15,%16,%17,%18,%19,%20,%21,%22,%23,%24,%25,%26,%27,%28,%29,%30,%31,%32,%33,%34,%35,%36,%37,%38,%39,%40,%41,%42,%43,%44,%45,%46,%47,%48,%49,%50,%51,%52,%53,%54,%55,%56,%57,%58,%59,%60,%61,%62,%63,%64,%65,%66,%67,%68,%69,%70,%71,%72,%73,%74,%75,%76,%77,%78,%79,%80,%81,%82,%83,%84,%85,%86,%87,%88,%89,%90,%91,%92,%93,%94,%95}, da, db, 1, 1, 1, 0, %98;}"
    : "+f"(d[0]),"+f"(d[1]),"+f"(d[2]),"+f"(d[3]),"+f"(d[4]),"+f"(d[5]),"+f"(d[6]),"+f"(d[7]),"+f"(d[8]),"+f"(d[9]),"+f"(d[10]),"+f"(d[11]),"+f"(d[12]),"+f"(d[13]),"+f"(d[14]),"+f"(d[15]),"+f"(d[16]),"+f"(d[17]),"+f"(d[18]),"+f"(d[19]),"+f"(d[20]),"+f"(d[21]),"+f"(d[22]),"+f"(d[23]),"+f"(d[24]),"+f"(d[25]),"+f"(d[26]),"+f"(d[27]),"+f"(d[28]),"+f"(d[29]),"+f"(d[30]),"+f"(d[31]),"+f"(d[32]),"+f"(d[33]),"+f"(d[34]),"+f"(d[35]),"+f"(d[36]),"+f"(d[37]),"+f"(d[38]),"+f"(d[39]),"+f"(d[40]),"+f"(d[41]),"+f"(d[42]),"+f"(d[43]),"+f"(d[44]),"+f"(d[45]),"+f"(d[46]),"+f"(d[47]),"+f"(d[48]),"+f"(d[49]),"+f"(d[50]),"+f"(d[51]),"+f"(d[52]),"+f"(d[53]),"+f"(d[54]),"+f"(d[55]),"+f"(d[56]),"+f"(d[57]),"+f"(d[58]),"+f"(d[59]),"+f"(d[60]),"+f"(d[61]),"+f"(d[62]),"+f"(d[63]),"+f"(d[64]),"+f"(d[65]),"+f"(d[66]),"+f"(d[67]),"+f"(d[68]),"+f"(d[69]),"+f"(d[70]),"+f"(d[71]),"+f"(d[72]),"+f"(d[73]),"+f"(d[74]),"+f"(d[75]),"+f"(d[76]),"+f"(d[77]),"+f"(d[78]),"+f"(d[79]),"+f"(d[80]),"+f"(d[81]),"+f"(d[82]),"+f"(d[83]),"+f"(d[84]),"+f"(d[85]),"+f"(d[86]),"+f"(d[87]),"+f"(d[88]),"+f"(d[89]),"+f"(d[90]),"+f"(d[91]),"+f"(d[92]),"+f"(d[93]),"+f"(d[94]),"+f"(d[95])
    : "r"(da), "r"(db), "n"(TB), "n"(HB));
}
template<int TB, uint32_t HB> __device__ __forceinline__ void wgmma_ss_n240(float (&d)[120], uint32_t da, uint32_t db) {
  asm volatile("{.reg .b64 da, db; mov.b64 da, {%120, %123}; mov.b64 db, {%121, %123};\nwgmma.mma_async.sync.aligned.m64n240k16.f32.bf16.bf16 "
    "{%0,%1,%2,%3,%4,%5,%6,%7,%8,%9,%10,%11,%12,%13,%14,%15,%16,%17,%18,%19,%20,%21,%22,%23,%24,%25,%26,%27,%28,%29,%30,%31,%32,%33,%34,%35,%36,%37,%38,%39,%40,%41,%42,%43,%44,%45,%46,%47,%48,%49,%50,%51,%52,%53,%54,%55,%56,%57,%58,%59,%60,%61,%62,%63,%64,%65,%66,%67,%68,%69,%70,%71,%72,%73,%74,%75,%76,%77,%78,%79,%80,%81,%82,%83,%84,%85,%86,%87,%88,%89,%90,%91,%92,%93,%94,%95,%96,%97,%98,%99,%100,%101,%102,%103,%104,%105,%106,%107,%108,%109,%110,%111,%112,%113,%114,%115,%116,%117,%118,%119}, da, db, 1, 1, 1, 0, %122;}"
    : "+f"(d[0]),"+f"(d[1]),"+f"(d[2]),"+f"(d[3]),"+f"(d[4]),"+f"(d[5]),"+f"(d[6]),"+f"(d[7]),"+f"(d[8]),"+f"(d[9]),"+f"(d[10]),"+f"(d[11]),"+f"(d[12]),"+f"(d[13]),"+f"(d[14]),"+f"(d[15]),"+f"(d[16]),"+f"(d[17]),"+f"(d[18]),"+f"(d[19]),"+f"(d[20]),"+f"(d[21]),"+f"(d[22]),"+f"(d[23]),"+f"(d[24]),"+f"(d[25]),"+f"(d[26]),"+f"(d[27]),"+f"(d[28]),"+f"(d[29]),"+f"(d[30]),"+f"(d[31]),"+f"(d[32]),"+f"(d[33]),"+f"(d[34]),"+f"(d[35]),"+f"(d[36]),"+f"(d[37]),"+f"(d[38]),"+f"(d[39]),"+f"(d[40]),"+f"(d[41]),"+f"(d[42]),"+f"(d[43]),"+f"(d[44]),"+f"(d[45]),"+f"(d[46]),"+f"(d[47]),"+f"(d[48]),"+f"(d[49]),"+f"(d[50]),"+f"(d[51]),"+f"(d[52]),"+f"(d[53]),"+f"(d[54]),"+f"(d[55]),"+f"(d[56]),"+f"(d[57]),"+f"(d[58]),"+f"(d[59]),"+f"(d[60]),"+f"(d[61]),"+f"(d[62]),"+f"(d[63]),"+f"(d[64]),"+f"(d[65]),"+f"(d[66]),"+f"(d[67]),"+f"(d[68]),"+f"(d[69]),"+f"(d[70]),"+f"(d[71]),"+f"(d[72]),"+f"(d[73]),"+f"(d[74]),"+f"(d[75]),"+f"(d[76]),"+f"(d[77]),"+f"(d[78]),"+f"(d[79]),"+f"(d[80]),"+f"(d[81]),"+f"(d[82]),"+f"(d[83]),"+f"(d[84]),"+f"(d[85]),"+f"(d[86]),"+f"(d[87]),"+f"(d[88]),"+f"(d[89]),"+f"(d[90]),"+f"(d[91]),"+f"(d[92]),"+f"(d[93]),"+f"(d[94]),"+f"(d[95]),"+f"(d[96]),"+f"(d[97]),"+f"(d[98]),"+f"(d[99]),"+f"(d[100]),"+f"(d[101]),"+f"(d[102]),"+f"(d[103]),"+f"(d[104]),"+f"(d[105]),"+f"(d[106]),"+f"(d[107]),"+f"(d[108]),"+f"(d[109]),"+f"(d[110]),"+f"(d[111]),"+f"(d[112]),"+f"(d[113]),"+f"(d[114]),"+f"(d[115]),"+f"(d[116]),"+f"(d[117]),"+f"(d[118]),"+f"(d[119])
    : "r"(da), "r"(db), "n"(TB), "n"(HB));
}
template<int TB, uint32_t HB> __device__ __forceinline__ void wgmma_ss_n240_z(float (&d)[120], uint32_t da, uint32_t db) {
  asm volatile("{.reg .b64 da, db; mov.b64 da, {%120, %123}; mov.b64 db, {%121, %123};\nwgmma.mma_async.sync.aligned.m64n240k16.f32.bf16.bf16 "
    "{%0,%1,%2,%3,%4,%5,%6,%7,%8,%9,%10,%11,%12,%13,%14,%15,%16,%17,%18,%19,%20,%21,%22,%23,%24,%25,%26,%27,%28,%29,%30,%31,%32,%33,%34,%35,%36,%37,%38,%39,%40,%41,%42,%43,%44,%45,%46,%47,%48,%49,%50,%51,%52,%53,%54,%55,%56,%57,%58,%59,%60,%61,%62,%63,%64,%65,%66,%67,%68,%69,%70,%71,%72,%73,%74,%75,%76,%77,%78,%79,%80,%81,%82,%83,%84,%85,%86,%87,%88,%89,%90,%91,%92,%93,%94,%95,%96,%97,%98,%99,%100,%101,%102,%103,%104,%105,%106,%107,%108,%109,%110,%111,%112,%113,%114,%115,%116,%117,%118,%119}, da, db, 0, 1, 1, 0, %122;}"
    : "=f"(d[0]),"=f"(d[1]),"=f"(d[2]),"=f"(d[3]),"=f"(d[4]),"=f"(d[5]),"=f"(d[6]),"=f"(d[7]),"=f"(d[8]),"=f"(d[9]),"=f"(d[10]),"=f"(d[11]),"=f"(d[12]),"=f"(d[13]),"=f"(d[14]),"=f"(d[15]),"=f"(d[16]),"=f"(d[17]),"=f"(d[18]),"=f"(d[19]),"=f"(d[20]),"=f"(d[21]),"=f"(d[22]),"=f"(d[23]),"=f"(d[24]),"=f"(d[25]),"=f"(d[26]),"=f"(d[27]),"=f"(d[28]),"=f"(d[29]),"=f"(d[30]),"=f"(d[31]),"=f"(d[32]),"=f"(d[33]),"=f"(d[34]),"=f"(d[35]),"=f"(d[36]),"=f"(d[37]),"=f"(d[38]),"=f"(d[39]),"=f"(d[40]),"=f"(d[41]),"=f"(d[42]),"=f"(d[43]),"=f"(d[44]),"=f"(d[45]),"=f"(d[46]),"=f"(d[47]),"=f"(d[48]),"=f"(d[49]),"=f"(d[50]),"=f"(d[51]),"=f"(d[52]),"=f"(d[53]),"=f"(d[54]),"=f"(d[55]),"=f"(d[56]),"=f"(d[57]),"=f"(d[58]),"=f"(d[59]),"=f"(d[60]),"=f"(d[61]),"=f"(d[62]),"=f"(d[63]),"=f"(d[64]),"=f"(d[65]),"=f"(d[66]),"=f"(d[67]),"=f"(d[68]),"=f"(d[69]),"=f"(d[70]),"=f"(d[71]),"=f"(d[72]),"=f"(d[73]),"=f"(d[74]),"=f"(d[75]),"=f"(d[76]),"=f"(d[77]),"=f"(d[78]),"=f"(d[79]),"=f"(d[80]),"=f"(d[81]),"=f"(d[82]),"=f"(d[83]),"=f"(d[84]),"=f"(d[85]),"=f"(d[86]),"=f"(d[87]),"=f"(d[88]),"=f"(d[89]),"=f"(d[90]),"=f"(d[91]),"=f"(d[92]),"=f"(d[93]),"=f"(d[94]),"=f"(d[95]),"=f"(d[96]),"=f"(d[97]),"=f"(d[98]),"=f"(d[99]),"=f"(d[100]),"=f"(d[101]),"=f"(d[102]),"=f"(d[103]),"=f"(d[104]),"=f"(d[105]),"=f"(d[106]),"=f"(d[107]),"=f"(d[108]),"=f"(d[109]),"=f"(d[110]),"=f"(d[111]),"=f"(d[112]),"=f"(d[113]),"=f"(d[114]),"=f"(d[115]),"=f"(d[116]),"=f"(d[117]),"=f"(d[118]),"=f"(d[119])
    : "r"(da), "r"(db), "n"(TB), "n"(HB));
}

__device__ __forceinline__ void wg_fence() { asm volatile("wgmma.fence.sync.aligned;" ::: "memory"); }
__device__ __forceinline__ void wg_commit() { asm volatile("wgmma.commit_group.sync.aligned;" ::: "memory"); }
template<int N> __device__ __forceinline__ void wg_wait() { asm volatile("wgmma.wait_group.sync.aligned %0;" :: "n"(N) : "memory"); }
__device__ __forceinline__ uint32_t mkdesc(uint32_t saddr, uint32_t lbo) { return ((saddr & 0x3FFFF) >> 4) | ((lbo >> 4) << 16); }
constexpr uint32_t SBO128 = 128 >> 4, SBO256 = 256 >> 4, SW128 = (1024 >> 4) | (1u << 30);
__device__ __forceinline__ uint32_t s2u(const void* p) { return (uint32_t)__cvta_generic_to_shared(p); }
__device__ __forceinline__ void mbar_init(uint32_t bar, uint32_t cnt) { asm volatile("mbarrier.init.shared::cta.b64 [%0], %1;" :: "r"(bar), "r"(cnt)); }
__device__ __forceinline__ void mbar_expect(uint32_t bar, uint32_t bytes) { asm volatile("mbarrier.arrive.expect_tx.shared::cta.b64 _, [%0], %1;" :: "r"(bar), "r"(bytes) : "memory"); }
__device__ __forceinline__ void mbar_arrive(uint32_t bar) { asm volatile("mbarrier.arrive.shared::cta.b64 _, [%0];" :: "r"(bar) : "memory"); }
__device__ __forceinline__ void mbar_arrive_cl(uint32_t cbar) { asm volatile("mbarrier.arrive.shared::cluster.b64 _, [%0];" :: "r"(cbar) : "memory"); }
__device__ __forceinline__ uint32_t mapa(uint32_t a, uint32_t rank) { uint32_t r; asm("mapa.shared::cluster.u32 %0, %1, %2;" : "=r"(r) : "r"(a), "r"(rank)); return r; }
__device__ __forceinline__ void mbar_wait(uint32_t bar, uint32_t par) {
  asm volatile("{\n.reg .pred p;\n.reg .u32 c;\nmov.u32 c, 0;\nLW:\nmbarrier.try_wait.parity.shared::cta.b64 p, [%0], %1;\n@p bra LD;\n"
               "add.u32 c, c, 1;\nsetp.lt.u32 p, c, 2000000;\n@p bra LW;\ntrap;\nLD:\n}" :: "r"(bar), "r"(par) : "memory");
}
__device__ __forceinline__ uint32_t enc_f(float v) { const uint32_t u = ~__float_as_uint(v); return u ? u : 0x80000000u; }
__device__ __forceinline__ void st_enc4(void* p, float a, float b, float c, float d) {
  asm volatile("st.relaxed.gpu.global.v4.u32 [%0], {%1, %2, %3, %4};" :: "l"(p), "r"(enc_f(a)), "r"(enc_f(b)), "r"(enc_f(c)), "r"(enc_f(d)) : "memory");
}
__device__ __forceinline__ unsigned ld_acq(const unsigned* p) {
  unsigned v; asm volatile("ld.acquire.gpu.global.u32 %0, [%1];" : "=r"(v) : "l"(p) : "memory"); return v;
}
__device__ __forceinline__ uint4 ld_rlx4(const void* p) {
  uint4 v; asm volatile("ld.relaxed.gpu.global.v4.u32 {%0, %1, %2, %3}, [%4];" : "=r"(v.x), "=r"(v.y), "=r"(v.z), "=r"(v.w) : "l"(p) : "memory"); return v;
}
__device__ __forceinline__ float4 poll_dec4(const void* p, uint4 v) {
  for (int it = 0; !(v.x && v.y && v.z && v.w); it++) { if (it > 2000000) __trap(); v = ld_rlx4(p); }
  return make_float4(__uint_as_float(~v.x), __uint_as_float(~v.y), __uint_as_float(~v.z), __uint_as_float(~v.w));
}
__device__ __forceinline__ void stsm4(uint32_t a, const uint32_t (&r)[4]) {
  asm volatile("stmatrix.sync.aligned.m8n8.x4.shared.b16 [%0], {%1, %2, %3, %4};" :: "r"(a), "r"(r[0]), "r"(r[1]), "r"(r[2]), "r"(r[3]) : "memory");
}
template<int N> __device__ __forceinline__ void reg_inc() { asm volatile("setmaxnreg.inc.sync.aligned.u32 %0;" :: "n"(N)); }
template<int N> __device__ __forceinline__ void reg_dec() { asm volatile("setmaxnreg.dec.sync.aligned.u32 %0;" :: "n"(N)); }
__device__ __forceinline__ void mbar_arrive_cl4(uint32_t cbar) { asm volatile("mbarrier.arrive.shared::cluster.b64 _, [%0], 4;" :: "r"(cbar) : "memory"); }
__device__ __forceinline__ void fence_async_smem() { asm volatile("fence.proxy.async.shared::cta;" ::: "memory"); }
__device__ __forceinline__ void bulk_s2peer(uint32_t dst, uint32_t src, uint32_t bytes, uint32_t bar) {
  asm volatile("cp.async.bulk.shared::cluster.shared::cta.mbarrier::complete_tx::bytes [%0], [%1], %2, [%3];" :: "r"(dst), "r"(src), "r"(bytes), "r"(bar) : "memory");
}
__device__ __forceinline__ void flag_release(unsigned* f) { asm volatile("st.release.gpu.global.u32 [%0], %1;" :: "l"(f), "r"(1u) : "memory"); }
__device__ __forceinline__ void bulk_g2s(uint32_t dst, const void* src, uint32_t bytes, uint32_t bar) {
  asm volatile("cp.async.bulk.shared::cluster.global.mbarrier::complete_tx::bytes [%0], [%1], %2, [%3];" :: "r"(dst), "l"(src), "r"(bytes), "r"(bar) : "memory");
}
__device__ __forceinline__ void bulk_g2s_mc(uint32_t dst, const void* src, uint32_t bytes, uint32_t bar) {
  asm volatile("cp.async.bulk.shared::cluster.global.mbarrier::complete_tx::bytes.multicast::cluster [%0], [%1], %2, [%3], %4;"
               :: "r"(dst), "l"(src), "r"(bytes), "r"(bar), "h"((uint16_t)3) : "memory");
}
__device__ __forceinline__ bool elect() { uint32_t e; asm volatile("{.reg .pred p; elect.sync _|p, 0xffffffff; selp.u32 %0, 1, 0, p;}" : "=r"(e)); return e; }
__device__ __forceinline__ void tma2d(uint32_t dst, const CUtensorMap* m, int c0, int c1, uint32_t bar) {
  asm volatile("cp.async.bulk.tensor.2d.shared::cluster.global.mbarrier::complete_tx::bytes [%0], [%1, {%3, %4}], [%2];"
               :: "r"(dst), "l"(m), "r"(bar), "r"(c0), "r"(c1) : "memory");
}
__device__ __forceinline__ void tma2d_mc(uint32_t dst, const CUtensorMap* m, int c0, int c1, uint32_t bar) {
  asm volatile("cp.async.bulk.tensor.2d.shared::cluster.global.mbarrier::complete_tx::bytes.multicast::cluster [%0], [%1, {%3, %4}], [%2], %5;"
               :: "r"(dst), "l"(m), "r"(bar), "r"(c0), "r"(c1), "h"((uint16_t)3) : "memory");
}
__device__ __forceinline__ void cluster_sync() { asm volatile("barrier.cluster.arrive.relaxed.aligned;\nbarrier.cluster.wait.aligned;" ::: "memory"); }
__device__ __forceinline__ void pdl_launch() { asm volatile("griddepcontrol.launch_dependents;"); }
__device__ __forceinline__ void pdl_wait() { asm volatile("griddepcontrol.wait;" ::: "memory"); }
__device__ __forceinline__ void bar_arrive(int id, int n) { asm volatile("bar.arrive %0, %1;" :: "r"(id), "r"(n) : "memory"); }
__device__ __forceinline__ void bar_sync(int id, int n) { asm volatile("bar.sync %0, %1;" :: "r"(id), "r"(n) : "memory"); }
template<int N> __device__ __forceinline__ void fence_f(float (&d)[N]) {
  #pragma unroll
  for (int i = 0; i < N; i++) asm volatile("" : "+f"(d[i]) :: "memory");
}
template<int N, int M> __device__ __forceinline__ void fence_u(uint32_t (&d)[N][M]) {
  #pragma unroll
  for (int i = 0; i < N; i++)
    #pragma unroll
    for (int j = 0; j < M; j++) asm volatile("" : "+r"(d[i][j]) :: "memory");
}
__device__ __forceinline__ float ex2(float x) { float y; asm("ex2.approx.ftz.f32 %0, %1;" : "=f"(y) : "f"(x)); return y; }
__device__ __forceinline__ float sqrt_fast(float x) { float y; asm("sqrt.approx.f32 %0, %1;" : "=f"(y) : "f"(x)); return y; }
__device__ __forceinline__ float rcp_fast(float x) { float y; asm("rcp.approx.f32 %0, %1;" : "=f"(y) : "f"(x)); return y; }
__device__ __forceinline__ uint32_t pack_bf16(float lo, float hi) { uint32_t r; asm("cvt.rn.bf16x2.f32 %0, %1, %2;" : "=r"(r) : "f"(hi), "f"(lo)); return r; }
__device__ __forceinline__ uint32_t pack_bf16_relu(float lo, float hi) { uint32_t r; asm("cvt.rn.relu.bf16x2.f32 %0, %1, %2;" : "=r"(r) : "f"(hi), "f"(lo)); return r; }
__device__ __forceinline__ uint32_t sq_bf16x2(uint32_t a) { uint32_t r; asm("mul.rn.bf16x2 %0, %1, %1;" : "=r"(r) : "r"(a)); return r; }
__device__ __forceinline__ float bf_lo(uint32_t v) { return __uint_as_float(v << 16); }
__device__ __forceinline__ float bf_hi(uint32_t v) { return __uint_as_float(v & 0xFFFF0000u); }
__device__ __forceinline__ float2 lds64(uint32_t a) { float2 v; asm volatile("ld.shared.v2.f32 {%0, %1}, [%2];" : "=f"(v.x), "=f"(v.y) : "r"(a)); return v; }
__device__ __forceinline__ float4 lds128(uint32_t a) { float4 v; asm volatile("ld.shared.v4.f32 {%0, %1, %2, %3}, [%4];" : "=f"(v.x), "=f"(v.y), "=f"(v.z), "=f"(v.w) : "r"(a)); return v; }
__device__ __forceinline__ uint32_t lds32(uint32_t a) { uint32_t v; asm volatile("ld.shared.u32 %0, [%1];" : "=r"(v) : "r"(a)); return v; }
__device__ __forceinline__ void stg128(void* p, const float4& v) { asm volatile("st.global.v4.f32 [%0], {%1, %2, %3, %4};" :: "l"(p), "f"(v.x), "f"(v.y), "f"(v.z), "f"(v.w) : "memory"); }
__device__ __forceinline__ uint4 ldg128(const void* p) { uint4 v; asm volatile("ld.global.nc.v4.u32 {%0, %1, %2, %3}, [%4];" : "=r"(v.x), "=r"(v.y), "=r"(v.z), "=r"(v.w) : "l"(p)); return v; }
__device__ __forceinline__ void stg32(void* p, uint32_t v) { asm volatile("st.global.u32 [%0], %1;" :: "l"(p), "r"(v) : "memory"); }

__device__ __forceinline__ uint32_t exp2_pair_poly(float a0, float a1, uint32_t mk) {
  uint32_t u, g, e, p;
  asm("prmt.b32 %0, %1, %2, 0x6521;" : "=r"(u) : "r"(__float_as_uint(a0)), "r"(__float_as_uint(a1)));
  asm("lop3.b32 %0, %1, %2, 0x3F003F00, 0xEA;" : "=r"(g) : "r"(u), "r"(mk));
  asm("lop3.b32 %0, %1, %2, 0x00030003, 0xBA;" : "=r"(e) : "r"(u), "r"(mk));
  asm("fma.rn.bf16x2 %0, %1, %2, %3;" : "=r"(p) : "r"(g), "r"(u), "r"(e));
  return p;
}
__device__ __forceinline__ void spin(uint32_t n) { const uint32_t t0 = clock(); while ((uint32_t)clock() - t0 < n) {} }
template<int V> struct IC { static constexpr int value = V; };

constexpr int K1_ST = 4, K1_STAGE = 49152, K1_SMEM = K1_ST * K1_STAGE + 1024;
__global__ void __launch_bounds__(384, 1) k1_qkv(const __grid_constant__ CUtensorMap mx, const __grid_constant__ CUtensorMap mw,
                                                 const __nv_bfloat16* __restrict__ x, const __nv_bfloat16* __restrict__ wqkv) {
  extern __shared__ uint8_t smem_raw[];
  __shared__ __align__(8) uint64_t bars[2 * K1_ST];
  __shared__ __align__(16) float2 t_cs[120];
  __shared__ __align__(16) float2 t_st[128];
  __shared__ __align__(16) float t_red[720];
  pdl_launch();
  const int tid = threadIdx.x, w8 = __shfl_sync(~0u, tid >> 5, 0), lane = tid & 31;
  const int rank = blockIdx.x & 1, nt = (blockIdx.x >> 1) & 7, rb = (blockIdx.x >> 4) * 2 + rank;
  const uint32_t sb = (s2u(smem_raw) + 1023) & ~1023u, fb = s2u(bars), eb = fb + 8 * K1_ST;
  if (tid == 64) {
    asm volatile("prefetch.tensormap [%0];" :: "l"(&mx) : "memory");
    asm volatile("prefetch.tensormap [%0];" :: "l"(&mw) : "memory");
  }
  if (tid == 0) {
    STAMP(1, 0);
    for (int i = 0; i < K1_ST; i++) { mbar_init(fb + 8 * i, 1); mbar_init(eb + 8 * i, 16); }
    asm volatile("fence.mbarrier_init.release.cluster;" ::: "memory");
  }
  cluster_sync();
  auto sum8 = [](const uint4& v) { return ((bf_lo(v.x) + bf_hi(v.x)) + (bf_lo(v.y) + bf_hi(v.y))) + ((bf_lo(v.z) + bf_hi(v.z)) + (bf_lo(v.w) + bf_hi(v.w))); };
  auto sq2 = [](uint32_t v, float m) { const float a = bf_lo(v) - m, b = bf_hi(v) - m; return a * a + b * b; };
  if (__any_sync(~0u, tid >= 256)) {
    reg_dec<152>();
    const int hw = w8 - 8;
    auto load_stage = [&](int kb) {
      const int s = kb & 3;
      const uint32_t d = sb + s * K1_STAGE, bar = fb + 8 * s;
      mbar_expect(bar, K1_STAGE);
      tma2d_mc(d + 16384 + (2 * rank) * 8192, &mw, nt * 240 + (2 * rank) * 64, kb * 64, bar);
      tma2d_mc(d + 16384 + (2 * rank + 1) * 8192, &mw, nt * 240 + (2 * rank + 1) * 64, kb * 64, bar);
      tma2d(d, &mx, kb * 64, rb * 128, bar);
    };
    if (hw == 0) {
      if (lane == 0) STAMP(1, 8);
      #pragma unroll 1
      for (int kb = 0; kb < 10; kb++) {
        if (kb >= K1_ST) mbar_wait(eb + 8 * (kb & 3), ((kb >> 2) - 1) & 1);
        if (elect()) load_stage(kb);
        __syncwarp();
      }
    } else {
      const int t = tid - 288;
      {
        uint4 wv[14];
        const int ch = t % 30, rg = min(t / 30, 2);
        const __nv_bfloat16* wp = wqkv + (size_t)(rb * 40 + rg * 13) * (3 * DM) + nt * 240 + ch * 8;
        spin(WDL);
        #pragma unroll
        for (int i = 0; i < 13; i++) wv[i] = ldg128(wp + (size_t)(i + (rg > 0)) * (3 * DM));
        wv[13] = ldg128(wp + (size_t)13 * (3 * DM));
        if (rg) wv[13] = make_uint4(0, 0, 0, 0);
        if (t < 8) g_flag[rb * 64 + 8 * t + nt] = 0;
        if (t >= 32) ((uint4*)g_stat2)[(rb * 8 + nt) * 64 + t - 32] = make_uint4(0, 0, 0, 0);
        float cs[8];
        #pragma unroll
        for (int e = 0; e < 8; e++) cs[e] = 0.f;
        #pragma unroll
        for (int i = 0; i < 14; i++) {
          cs[0] += bf_lo(wv[i].x); cs[1] += bf_hi(wv[i].x); cs[2] += bf_lo(wv[i].y); cs[3] += bf_hi(wv[i].y);
          cs[4] += bf_lo(wv[i].z); cs[5] += bf_hi(wv[i].z); cs[6] += bf_lo(wv[i].w); cs[7] += bf_hi(wv[i].w);
        }
        if (tid == 352 && cs[0] + cs[7] != 1.2345f) STAMP(1, 12);
        if (t < 90) {
          *(float4*)(t_red + rg * 240 + ch * 8) = make_float4(cs[0], cs[1], cs[2], cs[3]);
          *(float4*)(t_red + rg * 240 + ch * 8 + 4) = make_float4(cs[4], cs[5], cs[6], cs[7]);
        }
        bar_sync(2, 96);
        if (t < 60) {
          const float4 a = *(const float4*)(t_red + 4 * t), b = *(const float4*)(t_red + 240 + 4 * t), c = *(const float4*)(t_red + 480 + 4 * t);
          st_enc4(g_csq + rb * (3 * DM) + nt * 240 + 4 * t, a.x + b.x + c.x, a.y + b.y + c.y, a.z + b.z + c.z, a.w + b.w + c.w);
        }
      }
      if (tid == 352) STAMP(1, 6);
      mbar_wait(fb + 8 * 2, 1);
      if (tid == 288) STAMP(1, 13);
      if (t < 60) {
        const float* p = g_csq + nt * 240 + 4 * t;
        float4 s;
        for (int it = 0;; it++) {
          uint4 v[16];
          #pragma unroll
          for (int q = 0; q < 16; q++) v[q] = ld_rlx4(p + q * (3 * DM));
          bool ok = true;
          s = make_float4(0.f, 0.f, 0.f, 0.f);
          #pragma unroll
          for (int q = 0; q < 16; q++) {
            ok = ok && v[q].x && v[q].y && v[q].z && v[q].w;
            s.x += __uint_as_float(~v[q].x); s.y += __uint_as_float(~v[q].y); s.z += __uint_as_float(~v[q].z); s.w += __uint_as_float(~v[q].w);
          }
          if (tid == 288 && it == 0) STAMP(1, 14);
          if (ok) break;
          if (it > 1000000) __trap();
        }
        *(float4*)(t_cs + 2 * t) = s;
      } else if (t >= 64) {
        const float2* p = g_stat1 + rb * 128 + 2 * (t - 64);
        const uint4 v0 = ld_rlx4(p), v1 = ld_rlx4(p + 64);
        *(float4*)(t_st + 2 * (t - 64)) = poll_dec4(p, v0);
        *(float4*)(t_st + 2 * (t - 64) + 64) = poll_dec4(p + 64, v1);
      }
      if (tid == 288) STAMP(1, 4);
      bar_arrive(1, 224); bar_arrive(4, 224);
    }
  } else {
    reg_inc<176>();
    const int wg = __any_sync(~0u, tid & 128) ? 1 : 0;
    float acc[120];
    const uint32_t da = mkdesc(sb + wg * 8192, 16), db = mkdesc(sb + 16384, 8192);
    const uint32_t eb_peer = mapa(eb, rank ^ 1), eb_own = mapa(eb, rank);
    const int xr = rb * 128 + nt * 16 + w8 * 2 + (lane >> 4);
    uint4 xv[5];
    spin(XDL);
    #pragma unroll
    for (int i = 0; i < 5; i++) xv[i] = ldg128(x + (size_t)xr * DM + (lane & 15) * 8 + i * 128);
    #pragma unroll
    for (int kb = 0; kb < 10; kb++) {
      const int s = kb & 3;
      mbar_wait(fb + 8 * s, (kb >> 2) & 1);
      if (kb == 0 && tid == 0) STAMP(1, 1);
      if (kb == 7 && wg) bar_sync(3, 256);
      wg_fence();
      #pragma unroll
      for (int k = 0; k < 4; k++) {
        const uint32_t a = da + ((s * K1_STAGE + k * 32) >> 4), b = db + ((s * K1_STAGE + k * 2048) >> 4);
        if (kb == 0 && k == 0) wgmma_ss_n240_z<1, SW128>(acc, a, b); else wgmma_ss_n240<1, SW128>(acc, a, b);
      }
      wg_commit();
      if (kb == 9 && !wg) bar_arrive(3, 256);
      if (kb >= 1 && kb - 1 + K1_ST < 10) {
        wg_wait<1>();
        if (lane == 0) { mbar_arrive_cl(eb_own + 8 * ((kb - 1) & 3)); mbar_arrive_cl(eb_peer + 8 * ((kb - 1) & 3)); }
      }
      if (kb == 3) {
        float m = (sum8(xv[0]) + sum8(xv[1])) + (sum8(xv[2]) + sum8(xv[3])) + sum8(xv[4]), q = 0.f;
        #pragma unroll
        for (int o = 8; o; o >>= 1) m += __shfl_xor_sync(~0u, m, o);
        m *= 1.f / DM;
        #pragma unroll
        for (int i = 0; i < 5; i++) q += (sq2(xv[i].x, m) + sq2(xv[i].y, m)) + (sq2(xv[i].z, m) + sq2(xv[i].w, m));
        #pragma unroll
        for (int o = 8; o; o >>= 1) q += __shfl_xor_sync(~0u, q, o);
        if (!(lane & 15)) asm volatile("st.relaxed.gpu.global.v2.u32 [%0], {%1, %2};" :: "l"(g_stat1 + xr), "r"(enc_f(m)), "r"(enc_f(rsqrtf(q * (1.f / DM) + 1e-5f))) : "memory");
        __syncwarp();
        if (tid == 0) STAMP(1, 5);
      }
    }
    wg_wait<0>();
    fence_f(acc);
    if (tid == 0) STAMP(1, 2);
    if (tid == 128) STAMP(1, 9);
    bar_sync(wg ? 4 : 1, 224);
    const int r = lane >> 2, c = lane & 3;
    const float2 st0 = t_st[w8 * 16 + r], st1 = t_st[w8 * 16 + r + 8];
    const bool poly0 = !((MUFU_MASK >> (2 * w8)) & 1), poly1 = !((MUFU_MASK >> (2 * w8 + 1)) & 1);
    const uint32_t ex_one = (c & 1) ? 0u : 0x00003F80u;
    const uint32_t tcs = s2u(t_cs) + c * 8;
    #pragma unroll
    for (int m = 0; m < 6; m++) {
      const int g = 12 * nt + 2 * m, type = g >> 5, head = g & 31;
      const float sc0 = type == 0 ? 0.32259642f : (type == 1 && poly0) ? 2.f : 1.f;
      const float sc1 = type == 0 ? 0.32259642f : (type == 1 && poly1) ? 2.f : 1.f;
      const float rs0 = st0.y * sc0, rs1 = st1.y * sc1;
      float v[5][4];
      uint32_t pk[5][2];
      #pragma unroll
      for (int jj = 0; jj < 5; jj++) {
        const int j = 5 * m + jj;
        const float2 cs = lds64(tcs + j * 32);
        v[jj][0] = (acc[4 * j + 0] - st0.x * cs.x) * rs0; v[jj][1] = (acc[4 * j + 1] - st0.x * cs.y) * rs0;
        v[jj][2] = (acc[4 * j + 2] - st1.x * cs.x) * rs1; v[jj][3] = (acc[4 * j + 3] - st1.x * cs.y) * rs1;
        pk[jj][0] = pack_bf16(v[jj][0], v[jj][1]); pk[jj][1] = pack_bf16(v[jj][2], v[jj][3]);
      }
      const bool isv = type == 2;
      uint8_t* const pb = g_qkv + (size_t)((head >> 1) * 16 + rb) * PAIR + lane * 4;
      uint8_t* const pe = pb + (isv ? 10240 + w8 * 768 : type * 16384 + w8 * 512);
      uint8_t* const po = pe + (isv ? 16384 : 6144);
      uint8_t* const pc = isv ? pe + 256 : pb + type * 16384 + 4096 + w8 * 256;
      const int g1 = isv ? 384 : 256;
      stg32(pe, pk[0][0]); stg32(pe + 128, pk[1][0]); stg32(pe + g1, pk[0][1]); stg32(pe + g1 + 128, pk[1][1]);
      stg32(pc, (isv && c >= 2) ? ex_one : pk[2][0]); stg32(pc + (isv ? 384 : 128), (isv && c >= 2) ? ex_one : pk[2][1]);
      stg32(po, pk[3][0]); stg32(po + 128, pk[4][0]); stg32(po + g1, pk[3][1]); stg32(po + g1 + 128, pk[4][1]);
      if (isv) { stg32(po + 256, c < 2 ? ex_one : pk[2][0]); stg32(po + 640, c < 2 ? ex_one : pk[2][1]); }
      if (type == 1) {
        float a0 = v[0][0] * v[0][0] + v[0][1] * v[0][1] + v[1][0] * v[1][0] + v[1][1] * v[1][1];
        float a1 = v[0][2] * v[0][2] + v[0][3] * v[0][3] + v[1][2] * v[1][2] + v[1][3] * v[1][3];
        float b0 = v[3][0] * v[3][0] + v[3][1] * v[3][1] + v[4][0] * v[4][0] + v[4][1] * v[4][1];
        float b1 = v[3][2] * v[3][2] + v[3][3] * v[3][3] + v[4][2] * v[4][2] + v[4][3] * v[4][3];
        const float t0 = v[2][0] * v[2][0] + v[2][1] * v[2][1], t1 = v[2][2] * v[2][2] + v[2][3] * v[2][3];
        if (c < 2) { a0 += t0; a1 += t1; } else { b0 += t0; b1 += t1; }
        float s0 = (c < 2 ? a0 : b0) + __shfl_xor_sync(~0u, c < 2 ? b0 : a0, 2);
        float s1 = (c < 2 ? a1 : b1) + __shfl_xor_sync(~0u, c < 2 ? b1 : a1, 2);
        float s = ((c & 1) ? s1 : s0) + __shfl_xor_sync(~0u, (c & 1) ? s0 : s1, 1);
        if ((c & 1) ? poly1 : poly0) s *= 0.25f;
        const uint32_t su = __float_as_uint(s) & 0x7FFFFFFFu;
        const uint32_t me = __reduce_max_sync(~0u, c < 2 ? su : 0u), mo = __reduce_max_sync(~0u, c < 2 ? 0u : su);
        if (lane < 2) g_kpart[(head + lane) * 128 + rb * 8 + w8] = __uint_as_float(lane ? mo : me);
      }
    }
    if (tid == 0) STAMP(1, 3);
    if (tid == 128) STAMP(1, 10);
  }
}

constexpr int K2_SMEM = 32 * CHUNK + 2048;
__device__ __forceinline__ void retile_items(const CUtensorMap* mo, const CUtensorMap* m1, const CUtensorMap* m2, int gw, uint32_t buf, uint32_t bar) {
  const int lane = threadIdx.x & 31, kk = lane & 7, q = lane >> 3;
  uint32_t ph = 0;
  const bool w1 = (gw & 7) < 3;
  const int first = (gw >> 3) * (w1 ? 3 : 5) + (gw & 7) - (w1 ? 0 : 3);
  float cs8[2][8];
  #pragma unroll
  for (int e = 0; e < 16; e++) cs8[e >> 3][e & 7] = 0.f;
  #pragma unroll 1
  for (int it = first; it < (w1 ? 240 : 340); it += (w1 ? 24 : 40)) {
    const int mat = w1 ? 1 : it < 100 ? 0 : 2;
    const int u = it - (mat == 2 ? 100 : 0);
    const int cs = w1 ? first : u % 10, kb = w1 ? u / 24 : u / 10;
    if (lane == 0) { mbar_expect(bar, 8192); tma2d(buf, mat == 0 ? mo : mat == 1 ? m1 : m2, cs * 64, kb * 64, bar); }
    uint8_t* d[2];
    int kstride;
    #pragma unroll
    for (int h = 0; h < 2; h++) {
      const int G = cs * 8 + h * 4 + q;
      if (mat == 1) d[h] = g_w1 + (size_t)(G / 24) * (80 * 3072) + (G % 24) * 128 + kk * 16;
      else d[h] = (mat == 0 ? g_wo + (size_t)(G / 10) * (80 * 1280) : g_w2 + (size_t)(G / 10) * (192 * 1280)) + (G % 10) * 128 + kk * 16;
    }
    kstride = mat == 1 ? 3072 : 1280;
    mbar_wait(bar, ph); ph ^= 1;
    #pragma unroll RTU
    for (int i = 0; i < 16; i++) {
      const int h = i & 1;
      int kg = kb * 8 + (i >> 1);
      if (mat == 0) { const int o = kg % 5; kg += o == 2 ? 2 : o > 2 ? -1 : 0; }
      const float4 f = lds128(buf + ((i >> 1) * 8 + kk) * 128 + (((h * 4 + q) ^ kk) << 4));
      *(float4*)(d[h] + kg * kstride) = f;
      const uint32_t a = __float_as_uint(f.x), b = __float_as_uint(f.y), c = __float_as_uint(f.z), e = __float_as_uint(f.w);
      cs8[h][0] += bf_lo(a); cs8[h][1] += bf_hi(a); cs8[h][2] += bf_lo(b); cs8[h][3] += bf_hi(b);
      cs8[h][4] += bf_lo(c); cs8[h][5] += bf_hi(c); cs8[h][6] += bf_lo(e); cs8[h][7] += bf_hi(e);
    }
    __syncwarp();
  }
  if (w1) {
    #pragma unroll
    for (int e = 0; e < 16; e++) {
      float& v = cs8[e >> 3][e & 7];
      v += __shfl_xor_sync(~0u, v, 1); v += __shfl_xor_sync(~0u, v, 2); v += __shfl_xor_sync(~0u, v, 4);
    }
    if (kk < 2) {
      float4* o = (float4*)(g_cs1 + (first * 8 + kk * 4 + q) * 8);
      o[0] = kk ? make_float4(cs8[1][0], cs8[1][1], cs8[1][2], cs8[1][3]) : make_float4(cs8[0][0], cs8[0][1], cs8[0][2], cs8[0][3]);
      o[1] = kk ? make_float4(cs8[1][4], cs8[1][5], cs8[1][6], cs8[1][7]) : make_float4(cs8[0][4], cs8[0][5], cs8[0][6], cs8[0][7]);
    }
  }
}

__global__ void __launch_bounds__(512, 1) k2_attn(const __grid_constant__ CUtensorMap mo, const __grid_constant__ CUtensorMap m1, const __grid_constant__ CUtensorMap m2) {
  extern __shared__ __align__(128) uint8_t smem[];
  __shared__ __align__(8) uint64_t bars[16];
  __shared__ uint32_t cst[1];
  pdl_launch();
  const int tid = threadIdx.x, w16 = __shfl_sync(~0u, tid >> 5, 0), wg = w16 >> 2, warp = w16 & 3, lane = tid & 31;
  if (tid == 0) STAMP(2, 0);
  const uint32_t sb = s2u(smem), bb = s2u(bars);
  if (tid < 16) {
    mbar_init(bb + 8 * tid, (tid == NBAR && blockIdx.x >= 4) ? 16 - NBAR : 1);
    if (tid == 0) cst[0] = 0x007F007Fu;
    asm volatile("fence.mbarrier_init.release.cluster;" ::: "memory");
    asm volatile("fence.proxy.async.shared::cta;" ::: "memory");
  }
  if (tid >= 128 && tid < 256) {
    const bool poly = !((MUFU_MASK >> ((tid >> 3) & 15)) & 1);
    *(uint4*)(smem + 32 * CHUNK + (tid - 128) * 16) = make_uint4(poly ? 0x44404000u : 0x00003F80u, poly ? 0x3BACC04Du : 0u, 0u, 0u);
    fence_async_smem();
  }
  __syncthreads();
  if (blockIdx.x < 4) {
    retile_items(&mo, &m1, &m2, blockIdx.x * 16 + w16, ((sb + 1023) & ~1023u) + w16 * 8192, bb + 8 * w16);
    if (tid == 0) STAMP(2, 3);
    return;
  }
  const int head = (blockIdx.x - 4) >> 2, qq = (blockIdx.x - 4) & 3, odd = head & 1;
  const int c = lane & 3;
  const bool exl = (c >> 1) != odd;
  const uint32_t mk = lds32(s2u(cst));
  uint32_t q[2][4];
  const uint8_t* src = g_qkv + (size_t)((head >> 1) * 16) * PAIR;
  const uint32_t kv = odd ? 20480 : 10240, ko = odd ? 0 : CHUNK, vo = CHUNK - ko;
  auto load_kv = [&](int i) {
    const uint32_t bar = bb + 8 * min(i, NBAR);
    mbar_expect(bar, 2 * CHUNK);
    bulk_g2s(sb + i * 2 * CHUNK, src + (size_t)i * PAIR + kv, 2 * CHUNK, bar);
  };
  const int jld = (w16 >= INIT && lane == 0) ? (w16 - INIT) / LPI : -1;
  auto next_block = [&](int j) {
    if (jld == j) load_kv(w16);
    __syncwarp();
    mbar_wait(bb + 8 * (j + 1), 0);
  };
  uint32_t qn[6];
  auto load_q = [&](int t) {
    const uint8_t* qb = src + (size_t)(qq * 4 + t * 2 + (wg >> 1)) * PAIR + lane * 4;
    const uint8_t* qa = qb + odd * 6144 + ((wg & 1) * 4 + warp) * 512;
    const uint8_t* qc = qb + 4096 + ((wg & 1) * 4 + warp) * 256;
    #pragma unroll
    for (int i = 0; i < 6; i++) asm volatile("ld.global.u32 %0, [%1];" : "=r"(qn[i]) : "l"(i < 4 ? qa + i * 128 : qc + (i - 4) * 128));
  };
  pdl_wait();
  if (tid == 0) STAMP(2, 1);
  if (tid == 480) {
    mbar_expect(bb, CHUNK); bulk_g2s(sb + ko, src + kv + ko, CHUNK, bb);
    mbar_expect(bb + 120, CHUNK); bulk_g2s(sb + vo, src + kv + vo, CHUNK, bb + 120);
    load_kv(1);
  }
  __syncwarp();
  load_q(0);
  float kn;
  {
    const uint4 kp = *(const uint4*)(g_kpart + head * 128 + lane * 4);
    kn = sqrt_fast(__uint_as_float(__reduce_max_sync(~0u, max(max(kp.x, kp.y), max(kp.z, kp.w))))) * 1.004f;
  }
  #pragma unroll 1
  for (int t = 0; t < 2; t++) {
    const int lr = (t * 4 + wg) * 64 + warp * 16;
    q[0][0] = qn[0]; q[0][1] = qn[2]; q[0][2] = qn[1]; q[0][3] = qn[3]; q[1][0] = exl ? 0u : qn[4]; q[1][1] = exl ? 0u : qn[5];
    bool slow;
    {
      auto sq2 = [](uint32_t v) { const float a = bf_lo(v), b = bf_hi(v); return a * a + b * b; };
      float n0 = sq2(q[0][0]) + sq2(q[0][2]) + sq2(q[1][0]);
      float n1 = sq2(q[0][1]) + sq2(q[0][3]) + sq2(q[1][1]);
      n0 += __shfl_xor_sync(~0u, n0, 1); n0 += __shfl_xor_sync(~0u, n0, 2);
      n1 += __shfl_xor_sync(~0u, n1, 1); n1 += __shfl_xor_sync(~0u, n1, 2);
      const float m0 = ceilf(sqrt_fast(n0) * kn), m1 = ceilf(sqrt_fast(n1) * kn);
      const uint32_t bad = !(m0 <= M_LIMIT && m1 <= M_LIMIT);
      uint32_t any;
      asm volatile("{.reg .pred p, q; setp.ne.u32 p, %1, 0; bar.red.or.pred q, %2, 128, p; selp.u32 %0, 1, 0, q;}" : "=r"(any) : "r"(bad), "r"(1 + wg) : "memory");
      slow = __any_sync(~0u, any);
      q[1][2] = (slow || c >= 2) ? 0u : c ? 0x3F803F80u : ((__float_as_uint(-m0) >> 16) | 0x3F800000u);
      q[1][3] = (slow || c >= 2) ? 0u : c ? 0x3F803F80u : ((__float_as_uint(-m1) >> 16) | 0x3F800000u);
    }
    float o[12], s[32];
    const int jlim = t ? 0 : NBAR;
    uint32_t p[4][4];
    #pragma unroll
    for (int i = 0; i < 12; i++) o[i] = 0.f;
    const uint32_t co = odd ? 0 : 10240;
    uint32_t dk0 = mkdesc(sb + (odd ? 2048 : CHUNK), 128), dk1 = mkdesc(sb + co, 32 * CHUNK - co), dv = mkdesc(sb + vo, 384);
    constexpr uint32_t KB = (2 * CHUNK) >> 4, KB1 = KB - (KB << 16);
    if (t == 0) mbar_wait(bb, 0);
    if (t == 0 && tid == 0) STAMP(2, 2);
    if (!slow) {
      fence_f(o); fence_u(q);
      wg_fence();
      wgmma_rs_n64_z<0, SBO256>(s, q[0], dk0);
      wgmma_rs_n64<0, SBO128>(s, q[1], dk1);
      wg_commit();
      if (t == 0) mbar_wait(bb + 120, 0);
      uint32_t p2[4][4];
      auto softmax = [&](auto half, uint32_t (&pp)[4][4]) {
        constexpr int HF = decltype(half)::value;
        wg_wait<1>();
        fence_f(s); fence_u(pp);
        #pragma unroll
        for (int n = 0; n < 8; n++) {
          if ((MUFU_MASK >> (n + 8 * HF)) & 1) {
            pp[n >> 1][(n & 1) * 2 + 0] = pack_bf16(ex2(s[4 * n + 0]), ex2(s[4 * n + 1]));
            pp[n >> 1][(n & 1) * 2 + 1] = pack_bf16(ex2(s[4 * n + 2]), ex2(s[4 * n + 3]));
          } else {
            pp[n >> 1][(n & 1) * 2 + 0] = exp2_pair_poly(s[4 * n + 0], s[4 * n + 1], mk);
            pp[n >> 1][(n & 1) * 2 + 1] = exp2_pair_poly(s[4 * n + 2], s[4 * n + 3], mk);
          }
        }
        fence_u(pp); fence_f(s);
        wg_fence();
      };
      auto pv = [&](auto half, uint32_t (&pp)[4][4]) {
        constexpr int HF = decltype(half)::value;
        #pragma unroll
        for (int kk = 0; kk < 4; kk++) wgmma_rs_n24<1, SBO128>(o, pp[kk], dv + (kk + 4 * HF) * (768 >> 4));
        wg_commit();
      };
      wg_commit();
      #pragma unroll 1
      for (int j = 0; j < 15; j++) {
        softmax(IC<0>(), p);
        wgmma_rs_n64_z<0, SBO256>(s, q[0], dk0 + (2048 >> 4));
        wgmma_rs_n64<0, SBO128>(s, q[1], dk1 + (1024 >> 4));
        wg_commit();
        pv(IC<0>(), p);
        if (j < jlim) next_block(j);
        softmax(IC<1>(), p2);
        dk0 += KB; dk1 += KB1;
        wgmma_rs_n64_z<0, SBO256>(s, q[0], dk0);
        wgmma_rs_n64<0, SBO128>(s, q[1], dk1);
        wg_commit();
        pv(IC<1>(), p2);
        dv += (2 * CHUNK) >> 4;
      }
      load_q(1);
      softmax(IC<0>(), p);
      wgmma_rs_n64_z<0, SBO256>(s, q[0], dk0 + (2048 >> 4));
      wgmma_rs_n64<0, SBO128>(s, q[1], dk1 + (1024 >> 4));
      wg_commit();
      pv(IC<0>(), p);
      softmax(IC<1>(), p2);
      pv(IC<1>(), p2);
      wg_wait<0>();
      fence_f(o); fence_u(p); fence_u(p2);
    } else {
      float mx0 = -INFINITY, mx1 = -INFINITY;
      if (t == 0) mbar_wait(bb + 120, 0);
      load_q(1);
      #pragma unroll 1
      for (int j = 0; j < 32; j++) {
        if (!(j & 1) && j && (j >> 1) - 1 < jlim) next_block((j >> 1) - 1);
        const uint32_t koff = (j >> 1) * KB + (j & 1) * (3072 >> 4);
        const uint32_t mask = MUFU_MASK >> (8 * (j & 1));
        fence_u(q);
        wg_fence();
        wgmma_rs_n64_z<0, SBO256>(s, q[0], dk0 + (j >> 1) * KB + (j & 1) * (2048 >> 4));
        wgmma_rs_n64<0, SBO128>(s, q[1], dk1 + (j >> 1) * KB1 + (j & 1) * (1024 >> 4));
        wg_commit();
        wg_wait<0>();
        fence_f(s);
        float b0 = mx0, b1 = mx1;
        #pragma unroll
        for (int n = 0; n < 8; n++) {
          const float f = ((mask >> n) & 1) ? 1.f : 0.5f;
          #pragma unroll
          for (int e = 0; e < 4; e++) s[4 * n + e] *= f;
          b0 = fmaxf(b0, fmaxf(s[4 * n], s[4 * n + 1])); b1 = fmaxf(b1, fmaxf(s[4 * n + 2], s[4 * n + 3]));
        }
        b0 = fmaxf(b0, __shfl_xor_sync(~0u, b0, 1)); b0 = fmaxf(b0, __shfl_xor_sync(~0u, b0, 2));
        b1 = fmaxf(b1, __shfl_xor_sync(~0u, b1, 1)); b1 = fmaxf(b1, __shfl_xor_sync(~0u, b1, 2));
        const float f0 = ex2(mx0 - b0), f1 = ex2(mx1 - b1);
        mx0 = b0; mx1 = b1;
        #pragma unroll
        for (int n = 0; n < 3; n++) { o[4 * n] *= f0; o[4 * n + 1] *= f0; o[4 * n + 2] *= f1; o[4 * n + 3] *= f1; }
        #pragma unroll
        for (int n = 0; n < 8; n++) {
          p[n >> 1][(n & 1) * 2 + 0] = pack_bf16(ex2(s[4 * n + 0] - b0), ex2(s[4 * n + 1] - b0));
          p[n >> 1][(n & 1) * 2 + 1] = pack_bf16(ex2(s[4 * n + 2] - b1), ex2(s[4 * n + 3] - b1));
        }
        fence_u(p); fence_f(o);
        wg_fence();
        #pragma unroll
        for (int kk = 0; kk < 4; kk++) wgmma_rs_n24<1, SBO128>(o, p[kk], dv + koff + kk * (768 >> 4));
        wg_commit();
        wg_wait<0>();
        fence_f(o);
      }
    }
    const int ll = (lane & ~3) | (odd ? 0 : 2);
    const float i0 = rcp_fast(__shfl_sync(~0u, o[8], ll)), i1 = rcp_fast(__shfl_sync(~0u, o[10], ll));
    const int row0 = qq * 512 + lr;
    uint8_t* op = g_o + (size_t)((row0 >> 6) * 80 + 5 * (head >> 1)) * 1024 + ((row0 & 63) >> 3) * 128 + lane * 4;
    stg32(op + odd * 2048, pack_bf16(o[0] * i0, o[1] * i0));
    stg32(op + odd * 2048 + 128, pack_bf16(o[2] * i1, o[3] * i1));
    stg32(op + odd * 2048 + 1024, pack_bf16(o[4] * i0, o[5] * i0));
    stg32(op + odd * 2048 + 1024 + 128, pack_bf16(o[6] * i1, o[7] * i1));
    if (!exl) { stg32(op + 4096, pack_bf16(o[8] * i0, o[9] * i0)); stg32(op + 4096 + 128, pack_bf16(o[10] * i1, o[11] * i1)); }
  }
  if (tid == 0) STAMP(2, 3);
}

constexpr unsigned long long P3ORD = 0xFEDCBA98756423ull;
__host__ __device__ constexpr int p3(int x) { return (int)(P3ORD >> (4 * x)) & 15; }
__host__ __device__ constexpr bool p3_first(int x) { for (int y = 0; y < x; y++) if (p3(y) >> 1 == p3(x) >> 1) return false; return true; }
__host__ __device__ constexpr int p3_push() { for (int y = 0; y < 14; y++) if (p3(y) == 3) return 15 + y; return 0; }
constexpr int ASLOT = 12288, BSLOT = 30720, K3_SMEM = 8 * ASLOT + 4 * BSLOT;
__global__ void __launch_bounds__(384, 1) k3_mlp(const __nv_bfloat16* __restrict__ x, const __nv_bfloat16* __restrict__ b1, const __nv_bfloat16* __restrict__ b2,
                                                 __nv_bfloat16* __restrict__ out) {
  extern __shared__ __align__(128) uint8_t smem[];
  __shared__ __align__(8) uint64_t bars[25];
  __shared__ __align__(128) uint4 t_c1[192];
  __shared__ __align__(16) float2 t_b2[40];
  const int tid = threadIdx.x, w8 = __shfl_sync(~0u, tid >> 5, 0), lane = tid & 31;
  const int rank = blockIdx.x & 1, nt = blockIdx.x & 7, pr = nt >> 1, rb = blockIdx.x >> 3;
  const uint32_t sa0 = s2u(smem), sbb = sa0 + 8 * ASLOT, bb = s2u(bars);
  const uint32_t fbb = bb + 128, ebb = bb + 160, tb = bb + 192;
  if (tid == 0) {
    STAMP(3, 0);
    for (int i = 0; i < 4; i++) {
      mbar_init(bb + 8 * i, 1); mbar_init(bb + 32 + 8 * i, 8); mbar_init(bb + 64 + 8 * i, 1); mbar_init(bb + 96 + 8 * i, 8);
      mbar_init(fbb + 8 * i, 1); mbar_init(ebb + 8 * i, 8);
    }
    mbar_init(tb, 32);
    asm volatile("fence.mbarrier_init.release.cluster;" ::: "memory");
  }
  cluster_sync();
  auto tile_of = [&](int i) { return i < 2 ? (nt ^ i) : 2 * ((pr + (i >> 1)) & 3) + (i & 1); };
  if (__any_sync(~0u, tid >= 256)) {
   reg_dec<56>();
   auto hid_flags = [&](int hf) {
     unsigned* const fw = g_flag + rb * 64 + 32 * hf + 8 + nt;
     bar_sync(7 + hf, 160);
     if (lane == 0) flag_release(fw);
     __syncwarp();
     if (lane == 0) STAMP(2, 14 + hf);
   };
   if (!(w8 & 1)) {
    const int g = (w8 >> 1) & 1, vb = 2 * rb + g;
    const uint32_t sa = sa0 + g * 4 * ASLOT, fa = bb + 64 * g, ea = fa + 32;
    const uint8_t* src; uint32_t bytes; int f = -1, mode = 2;
    const int ia = lane, s = ia & 3;
    if (ia < 8) { src = g_o + (size_t)(vb * 8 + ((2 * pr + ia) & 7)) * HBLK; bytes = HBLK; }
    else if (ia < 15) {
      f = tile_of(ia - 7);
      src = g_h + (size_t)(vb * 8 + f) * HBLK; bytes = HBLK;
      if (ia == 8) mode = 0;
    } else {
      const int u = p3(min(ia, 28) - 15), tl = tile_of(u >> 1);
      src = g_hid + (size_t)(vb * 16 + tl * 2 + (u & 1)) * ASLOT; bytes = ASLOT;
      f = 8 + tl;
      if (u < 4) mode = u != 3;
    }
    const uint32_t need = (f >= 0 && mode) ? 1u << f : 0u, off = mode == 2 ? rank * (bytes >> 1) : 0u;
    const uint32_t dst = sa + s * ASLOT + off;
    src += off;
    const unsigned* fp = g_flag + vb * 32 + lane;
    pdl_wait();
    if (tid == 256) STAMP(3, 1);
    if (__any_sync(~0u, g)) mbar_wait(bb, 0);
    auto push = [&](int ss, uint32_t n, int e) {
      mbar_wait(ea + 8 * (e & 3), ((e >> 2) - 1) & 1);
      if (elect()) bulk_s2peer(mapa(sa + (e & 3) * ASLOT, rank ^ 1), sa + ss * ASLOT, n, mapa(fa + 8 * (e & 3), rank ^ 1));
      __syncwarp();
    };
    uint32_t ready = 0;
    #pragma unroll 1
    for (int i = 0; i < 29; i++) {
      if (i == 8) {
        bar_sync(1 + g, 160);
        push(3, HBLK, 8);
      } else if (i == 15) {
        bar_sync(3 + g, 160);
        push(2, ASLOT, p3_push());
      } else if (i == 11 || i == 18) {
        const int e = i == 11 ? 8 : p3_push();
        mbar_wait(fa + 8 * (e & 3), (e >> 2) & 1);
        if (elect()) { mbar_arrive_cl4(mapa(ea + 8 * (i & 3), 0)); mbar_arrive_cl4(mapa(ea + 8 * (i & 3), 1)); }
        __syncwarp();
      }
      const uint32_t nd = __shfl_sync(~0u, need, i);
      if (nd & ~ready) {
        for (int it = 0; nd & ~ready; it++) {
          ready |= __ballot_sync(~0u, ld_acq(fp) != 0);
          if (it > 2000000) __trap();
        }
        asm volatile("fence.proxy.async.global;" ::: "memory");
      }
      const uint32_t ud = __shfl_sync(~0u, dst, i), up = __shfl_sync(~0u, bytes | (uint32_t)mode, i);
      const uint64_t us = __shfl_sync(~0u, (unsigned long long)src, i);
      const uint32_t ub = fa + 8 * (i & 3), un = up & ~3u, um = up & 3u;
      if (i >= 4) mbar_wait(ea + 8 * (i & 3), ((i >> 2) - 1) & 1);
      if (elect()) {
        mbar_expect(ub, un);
        if (um == 2) bulk_g2s_mc(ud, (const void*)us, un >> 1, ub);
        else if (um) bulk_g2s(ud, (const void*)us, un, ub);
      }
      __syncwarp();
    }
  } else if (w8 == 9) {
    {
      pdl_wait();
      #pragma unroll 1
      for (int ib = 0; ib < 20; ib++) {
        const int s = ib & 3;
        const uint8_t* src; uint32_t bytes = BSLOT;
        if (ib < 4) { src = g_wo + (size_t)(nt * 4 + ((pr + ib) & 3)) * 25600; bytes = 25600; }
        else if (ib < 12) src = g_w1 + (size_t)(nt * 8 + tile_of(ib - 4)) * BSLOT;
        else src = g_w2 + (size_t)(nt * 8 + tile_of(ib - 12)) * BSLOT;
        if (ib >= 1 && ib < 4) mbar_wait(bb + 8 * ((2 * ib - 2) & 3), (2 * ib - 2) >> 2);
        if (ib == 4) mbar_wait(bb + 8 * 2, 1);
        if (ib >= 4) mbar_wait(ebb + 8 * s, ((ib >> 2) - 1) & 1);
        if (elect()) {
          mbar_expect(fbb + 8 * s, bytes);
          bulk_g2s(sbb + s * BSLOT, src, bytes, fbb + 8 * s);
        }
        __syncwarp();
        if (ib == 15) hid_flags(1);
      }
    }
  } else {
    const uint4 bv = ldg128(b1 + nt * 192 + 8 * min(lane, 23));
    for (int e = lane; e < 40; e += 32) { const uint32_t u = *(const uint32_t*)(b2 + nt * 80 + 2 * e); t_b2[e] = make_float2(bf_lo(u), bf_hi(u)); }
    pdl_wait();
    if (lane < 24) {
      const int n = nt * 192 + 8 * lane;
      const float4 s0 = *(const float4*)(g_cs1 + n), s1 = *(const float4*)(g_cs1 + n + 4);
      const uint4 hi = make_uint4(pack_bf16(s0.x, s0.y), pack_bf16(s0.z, s0.w), pack_bf16(s1.x, s1.y), pack_bf16(s1.z, s1.w));
      const uint4 lo = make_uint4(pack_bf16(s0.x - bf_lo(hi.x), s0.y - bf_hi(hi.x)), pack_bf16(s0.z - bf_lo(hi.y), s0.w - bf_hi(hi.y)),
                                  pack_bf16(s1.x - bf_lo(hi.z), s1.y - bf_hi(hi.z)), pack_bf16(s1.z - bf_lo(hi.w), s1.w - bf_hi(hi.w)));
      const uint4 z = make_uint4(0, 0, 0, 0);
      uint4* t = t_c1 + lane * 8;
      t[0] = hi; t[1] = hi; t[2] = lo; t[3] = lo; t[4] = bv; t[5] = bv; t[6] = z; t[7] = z;
      fence_async_smem();
    }
    mbar_arrive(tb);
    {
      const uint4 z = make_uint4(0, 0, 0, 0);
      ((uint4*)g_csq)[blockIdx.x * 60 + lane] = z;
      if (lane < 28) ((uint4*)g_csq)[blockIdx.x * 60 + 32 + lane] = z;
      if (lane < 8) ((uint4*)g_stat1)[blockIdx.x * 8 + lane] = z;
    }
    __syncwarp();
    if (lane == 0) STAMP(0, 1);
    {
      #pragma unroll 1
      for (int g = 0; g < 2; g++) {
        bar_sync(12 + g, 160);
        if (lane == 0) flag_release(g_flag + (2 * rb + g) * 32 + nt);
        __syncwarp();
        if (lane == 0) STAMP(2, 12 + g);
      }
    }
    hid_flags(0);
   }
  } else {
    reg_inc<224>();
    const int wg = __any_sync(~0u, tid & 128) ? 1 : 0, r = lane >> 2, c = lane & 3;
    const uint32_t sa = sa0 + wg * 4 * ASLOT, fa = bb + 64 * wg, ea = fa + 32;
    const uint32_t ea_own = mapa(ea, rank), ea_peer = mapa(ea, rank ^ 1);
    auto rel_a = [&](int ia) { if (ia < 25 && lane == 0) { mbar_arrive_cl(ea_own + 8 * (ia & 3)); mbar_arrive_cl(ea_peer + 8 * (ia & 3)); } };
    auto rel_b = [&](int ib) { if (ib < 16 && lane == 0) mbar_arrive(ebb + 8 * (ib & 3)); };
    const uint32_t da = mkdesc(sa, 1024);
    const uint32_t db80 = mkdesc(sbb, 1280), db192 = mkdesc(sbb, 3072);
    const int row = rb * 128 + w8 * 16 + r;
    const uint32_t stg_a = sa + (lane >> 4) * 1024 + (w8 & 3) * 256 + (lane & 15) * 16;
    uint32_t hp[5][4];
    {
      const __nv_bfloat16* xp = x + (size_t)row * DM + nt * 80 + 2 * c;
      #pragma unroll
      for (int j = 0; j < 10; j++) {
        hp[j >> 1][(j & 1) * 2] = __ldg((const uint32_t*)(xp + 8 * j));
        hp[j >> 1][(j & 1) * 2 + 1] = __ldg((const uint32_t*)(xp + 8 * DM + 8 * j));
      }
    }
    float acc[40];
    #pragma unroll
    for (int i = 0; i < 8; i++) {
      if (!(i & 1)) mbar_wait(fbb + 8 * (i >> 1), 0);
      mbar_wait(fa + 8 * (i & 3), (i >> 2) & 1);
      if (i == 0 && tid == 0) STAMP(3, 2);
      if (i == 0 && tid == 128) STAMP(0, 2);
      wg_fence();
      #pragma unroll
      for (int k = 0; k < 5; k++) {
        const uint32_t a = da + (((i & 3) * ASLOT + k * 2048) >> 4), b = db80 + (((i >> 1) * BSLOT + (i & 1) * 12800 + k * 2560) >> 4);
        if (i == 0 && k == 0) wgmma_ss_n80_z<1, SBO128>(acc, a, b); else wgmma_ss_n80<1, SBO128>(acc, a, b);
      }
      wg_commit();
      if (i >= 1) { wg_wait<1>(); rel_a(i - 1); if (!(i & 1)) rel_b((i - 1) >> 1); }
    }
    wg_wait<0>();
    fence_f(acc);
    rel_b(3);
    uint8_t* const ph = g_h + (size_t)((2 * rb + wg) * 8 + nt) * HBLK + (w8 & 3) * 256 + lane * 4;
    if (tid == 0) STAMP(3, 3);
    if (tid == 128) STAMP(0, 3);
    #pragma unroll
    for (int j = 0; j < 10; j++) {
      uint32_t& u0 = hp[j >> 1][(j & 1) * 2];
      uint32_t& u1 = hp[j >> 1][(j & 1) * 2 + 1];
      acc[4 * j] += bf_lo(u0); acc[4 * j + 1] += bf_hi(u0); acc[4 * j + 2] += bf_lo(u1); acc[4 * j + 3] += bf_hi(u1);
      u0 = pack_bf16(acc[4 * j], acc[4 * j + 1]);
      u1 = pack_bf16(acc[4 * j + 2], acc[4 * j + 3]);
      stg32(ph + j * 1024, u0); stg32(ph + j * 1024 + 128, u1);
      if (j & 1) stsm4(stg_a + 3 * ASLOT + (j >> 1) * 2048, hp[j >> 1]);
    }
    bar_arrive(12 + wg, 160);
    fence_async_smem();
    bar_arrive(1 + wg, 160);
    if (tid == 0) STAMP(3, 4);
    float ac2[96];
    mbar_wait(fbb, 1);
    fence_u(hp);
    wg_fence();
    #pragma unroll
    for (int k = 0; k < 5; k++) {
      const uint32_t b = db192 + ((k * 6144) >> 4);
      if (k == 0) wgmma_rs_n192_z<1, SBO128>(ac2, hp[k], b); else wgmma_rs_n192<1, SBO128>(ac2, hp[k], b);
    }
    wg_commit();
    {
      float s0 = 0.f, s1 = 0.f, q0 = 0.f, q1 = 0.f;
      #pragma unroll
      for (int j = 0; j < 10; j++) { s0 += acc[4 * j] + acc[4 * j + 1]; s1 += acc[4 * j + 2] + acc[4 * j + 3]; }
      s0 += __shfl_xor_sync(~0u, s0, 1); s1 += __shfl_xor_sync(~0u, s1, 1);
      s0 += __shfl_xor_sync(~0u, s0, 2); s1 += __shfl_xor_sync(~0u, s1, 2);
      s0 *= 1.f / 80; s1 *= 1.f / 80;
      #pragma unroll
      for (int j = 0; j < 10; j++) {
        const float a = acc[4 * j] - s0, b = acc[4 * j + 1] - s0, d = acc[4 * j + 2] - s1, e = acc[4 * j + 3] - s1;
        q0 += a * a + b * b; q1 += d * d + e * e;
      }
      q0 += __shfl_xor_sync(~0u, q0, 1); q1 += __shfl_xor_sync(~0u, q1, 1);
      q0 += __shfl_xor_sync(~0u, q0, 2); q1 += __shfl_xor_sync(~0u, q1, 2);
      if (c < 2) asm volatile("st.relaxed.gpu.global.v2.u32 [%0], {%1, %2};" :: "l"(g_stat2 + (rb * 8 + nt) * 128 + w8 * 16 + r + 8 * c),
                              "r"(enc_f(c ? s1 : s0)), "r"(enc_f(c ? q1 : q0)) : "memory");
    }
    uint2 sv[4];
    auto stats_ok = [&]() { return sv[0].x && sv[0].y && sv[1].x && sv[1].y && sv[2].x && sv[2].y && sv[3].x && sv[3].y; };
    auto load_stats = [&]() {
      #pragma unroll
      for (int e = 0; e < 4; e++)
        asm volatile("ld.relaxed.gpu.global.v2.u32 {%0, %1}, [%2];" : "=r"(sv[e].x), "=r"(sv[e].y) : "l"(g_stat2 + (rb * 8 + 2 * c + (e >> 1)) * 128 + w8 * 16 + r + 8 * (e & 1)) : "memory");
    };
    float vr0, vr1;
    uint32_t ax[1][4];
    auto make_ax = [&]() {
      for (int it = 0; it < 1000000 && !stats_ok(); it++) load_stats();
      __syncwarp();
      float m[4], q[4];
      #pragma unroll
      for (int e = 0; e < 4; e++) { m[e] = __uint_as_float(~sv[e].x); q[e] = __uint_as_float(~sv[e].y); }
      float m0 = m[0] + m[2], m1 = m[1] + m[3];
      m0 += __shfl_xor_sync(~0u, m0, 1); m1 += __shfl_xor_sync(~0u, m1, 1);
      m0 += __shfl_xor_sync(~0u, m0, 2); m1 += __shfl_xor_sync(~0u, m1, 2);
      m0 *= 0.125f; m1 *= 0.125f;
      float v0 = q[0] + q[2] + 80.f * ((m[0] - m0) * (m[0] - m0) + (m[2] - m0) * (m[2] - m0));
      float v1 = q[1] + q[3] + 80.f * ((m[1] - m1) * (m[1] - m1) + (m[3] - m1) * (m[3] - m1));
      v0 += __shfl_xor_sync(~0u, v0, 1); v1 += __shfl_xor_sync(~0u, v1, 1);
      v0 += __shfl_xor_sync(~0u, v0, 2); v1 += __shfl_xor_sync(~0u, v1, 2);
      v0 = v0 * (1.f / DM) + 1e-5f; v1 = v1 * (1.f / DM) + 1e-5f;
      vr0 = rcp_fast(v0); vr1 = rcp_fast(v1);
      auto split = [](float v) { const float h = bf_lo(pack_bf16(v, 0.f)); return pack_bf16(h, v - h); };
      ax[0][0] = split(c < 2 ? -m0 : c == 2 ? sqrt_fast(v0) : 0.f); ax[0][1] = split(c < 2 ? -m1 : c == 2 ? sqrt_fast(v1) : 0.f); ax[0][2] = 0u; ax[0][3] = 0u;
      mbar_wait(tb, 0);
      fence_u(ax);
    };
    #pragma unroll
    for (int i = 1; i < 8; i++) {
      const int ia = 7 + i, ib = 4 + i;
      mbar_wait(fbb + 8 * (ib & 3), (ib >> 2) & 1);
      mbar_wait(fa + 8 * (ia & 3), (ia >> 2) & 1);
      if (i == HLD && wg) bar_sync(11, 256);
      if (i == 1 && tid == 0) STAMP(3, 5);
      if (i == 2 && tid == 0) STAMP(3, 11);
      if (i == 2 && tid == 128) STAMP(0, 11);
      if (i == 1 && tid == 128) STAMP(0, 5);
      if (i == 5 && tid == 128) STAMP(0, 15);
      if (i == 5 && tid == 0) STAMP(3, 15);
      wg_fence();
      if (i == XS) wgmma_rs_n192<1, SBO128>(ac2, ax[0], mkdesc(s2u(t_c1), 0));
      #pragma unroll
      for (int k = 0; k < 5; k++) wgmma_ss_n192<1, SBO128>(ac2, da + (((ia & 3) * ASLOT + k * 2048) >> 4), db192 + (((ib & 3) * BSLOT + k * 6144) >> 4));
      wg_commit();
      if (i == HAR && !wg) bar_arrive(11, 256);
      if (i == STL) load_stats();
      wg_wait<1>();
      if (i > 1) rel_a(ia - 1);
      rel_b(ib - 1);
      if (i == XS - 1) make_ax();
    }
    wg_wait<0>();
    fence_u(ax);
    fence_f(ac2); fence_u(hp);
    rel_b(11);
    uint8_t* const pd = g_hid + (size_t)((2 * rb + wg) * 16 + nt * 2) * ASLOT + (w8 & 3) * 256 + lane * 4;
    if (tid == 0) STAMP(3, 6);
    if (tid == 128) STAMP(0, 6);
    uint32_t hid[12][4];
    #pragma unroll
    for (int j = 0; j < 24; j++) {
      hid[j >> 1][(j & 1) * 2] = sq_bf16x2(pack_bf16_relu(ac2[4 * j], ac2[4 * j + 1]));
      hid[j >> 1][(j & 1) * 2 + 1] = sq_bf16x2(pack_bf16_relu(ac2[4 * j + 2], ac2[4 * j + 3]));
      stg32(pd + j * 1024, hid[j >> 1][(j & 1) * 2]); stg32(pd + j * 1024 + 128, hid[j >> 1][(j & 1) * 2 + 1]);
      if ((j & 1) && j >= 12) stsm4(stg_a + ASLOT + (j >> 1) * 2048, hid[j >> 1]);
      if (j == 23) { bar_arrive(7 + wg, 160); fence_async_smem(); bar_arrive(3 + wg, 160); }
    }
    if (tid == 0) STAMP(3, 7);
    mbar_wait(fbb, 1);
    fence_u(hid);
    wg_fence();
    #pragma unroll
    for (int k = 0; k < 12; k++) {
      const uint32_t b = db80 + ((k * 2560) >> 4);
      if (k == 0) wgmma_rs_n80_z<1, SBO128>(acc, hid[k], b); else wgmma_rs_n80<1, SBO128>(acc, hid[k], b);
    }
    wg_commit();
    wg_wait<0>();
    rel_b(12);
    #pragma unroll
    for (int y = 0; y < 14; y++) {
      const int ia = 15 + y, u = p3(y), ib = 12 + (u >> 1);
      if (p3_first(y)) mbar_wait(fbb + 8 * (ib & 3), (ib >> 2) & 1);
      mbar_wait(fa + 8 * (ia & 3), (ia >> 2) & 1);
      if (y == 0 && tid == 0) STAMP(3, 8);
      if (y == 0 && tid == 128) STAMP(0, 8);
      if ((y == 2 || y == 6 || y == 10) && tid == 128) STAMP(0, 12 + y / 4);
      if ((y == 2 || y == 6 || y == 10) && tid == 0) STAMP(3, 12 + y / 4);
      wg_fence();
      #pragma unroll
      for (int k = 0; k < 6; k++) wgmma_ss_n80<1, SBO128>(acc, da + (((ia & 3) * ASLOT + k * 2048) >> 4), db80 + (((ib & 3) * BSLOT + (u & 1) * 15360 + k * 2560) >> 4));
      wg_commit();
      wg_wait<1>();
      if (y == 0) fence_u(hid);
      else { rel_a(ia - 1); if (!p3_first(y - 1)) rel_b(12 + (p3(y - 1) >> 1)); }
    }
    wg_wait<0>();
    fence_f(acc);
    if (tid == 0) STAMP(3, 9);
    if (tid == 128) STAMP(0, 9);
    {
      const uint32_t t2 = s2u(t_b2) + c * 8;
      #pragma unroll
      for (int j = 0; j < 10; j++) {
        const float2 bv = lds64(t2 + j * 32);
        uint32_t& u0 = hp[j >> 1][(j & 1) * 2];
        uint32_t& u1 = hp[j >> 1][(j & 1) * 2 + 1];
        u0 = pack_bf16(fmaf(acc[4 * j], vr0, bv.x) + bf_lo(u0), fmaf(acc[4 * j + 1], vr0, bv.y) + bf_hi(u0));
        u1 = pack_bf16(fmaf(acc[4 * j + 2], vr1, bv.x) + bf_lo(u1), fmaf(acc[4 * j + 3], vr1, bv.y) + bf_hi(u1));
      }
      bar_sync(9 + wg, 128);
      const uint32_t stg = sa + (w8 & 3) * (16 * 176);
      #pragma unroll
      for (int k = 0; k < 5; k++) stsm4(stg + (lane & 15) * 176 + (2 * k + (lane >> 4)) * 16, hp[k]);
      __syncwarp();
      uint8_t* op = (uint8_t*)(out + (size_t)(rb * 128 + w8 * 16) * DM + nt * 80);
      #pragma unroll
      for (int k = 0; k < 5; k++) {
        const int id = k * 32 + lane, rr = id / 10, ch = id - rr * 10;
        stg128(op + rr * (DM * 2) + ch * 16, lds128(stg + rr * 176 + ch * 16));
      }
    }
    if (tid == 0) STAMP(3, 10);
    if (tid == 128) STAMP(0, 10);
  }
}

typedef CUresult (*EncodeFn)(CUtensorMap*, CUtensorMapDataType, cuuint32_t, void*, const cuuint64_t*, const cuuint64_t*, const cuuint32_t*, const cuuint32_t*,
                             CUtensorMapInterleave, CUtensorMapSwizzle, CUtensorMapL2promotion, CUtensorMapFloatOOBfill);

template<typename... KArgs, typename... Args>
void launch(void (*k)(KArgs...), int grid, int block, int smem, int cluster, bool pdl, Args... args) {
  cudaLaunchConfig_t cfg = {};
  cfg.gridDim = dim3(grid); cfg.blockDim = dim3(block); cfg.dynamicSmemBytes = smem; cfg.stream = cudaStreamPerThread;
  cudaLaunchAttribute at[2];
  int n = 0;
  if (cluster > 1) { at[n].id = cudaLaunchAttributeClusterDimension; at[n].val.clusterDim.x = cluster; at[n].val.clusterDim.y = 1; at[n].val.clusterDim.z = 1; n++; }
  if (pdl) { at[n].id = cudaLaunchAttributeProgrammaticStreamSerialization; at[n].val.programmaticStreamSerializationAllowed = 1; n++; }
  cfg.attrs = at; cfg.numAttrs = n;
  cudaLaunchKernelEx(&cfg, k, args...);
}

}

extern "C" void kernel_launch(void* const* d_in, const int* in_sizes, int n_in, void* d_out, int out_size) {
  const __nv_bfloat16* x = (const __nv_bfloat16*)d_in[0];
  const __nv_bfloat16* wqkv = (const __nv_bfloat16*)d_in[1];
  const __nv_bfloat16* wo = (const __nv_bfloat16*)d_in[2];
  const __nv_bfloat16* w1 = (const __nv_bfloat16*)d_in[4];
  const __nv_bfloat16* b1 = (const __nv_bfloat16*)d_in[5];
  const __nv_bfloat16* w2 = (const __nv_bfloat16*)d_in[6];
  const __nv_bfloat16* b2 = (const __nv_bfloat16*)d_in[7];
  static EncodeFn enc = nullptr;
  if (!enc) {
    void* fn = nullptr;
    cudaDriverEntryPointQueryResult qr;
    cudaGetDriverEntryPoint("cuTensorMapEncodeTiled", &fn, cudaEnableDefault, &qr);
    enc = (EncodeFn)fn;
    cudaFuncSetAttribute(k1_qkv, cudaFuncAttributeMaxDynamicSharedMemorySize, K1_SMEM);
    cudaFuncSetAttribute(k2_attn, cudaFuncAttributeMaxDynamicSharedMemorySize, K2_SMEM);
    cudaFuncSetAttribute(k3_mlp, cudaFuncAttributeMaxDynamicSharedMemorySize, K3_SMEM);
  }
  auto make_map = [&](const void* p, int cols, int rows, int box_rows) {
    CUtensorMap m;
    cuuint64_t dims[2] = {(cuuint64_t)cols, (cuuint64_t)rows}, st[1] = {(cuuint64_t)cols * 2};
    cuuint32_t box[2] = {64, (cuuint32_t)box_rows}, es[2] = {1, 1};
    enc(&m, CU_TENSOR_MAP_DATA_TYPE_BFLOAT16, 2, (void*)p, dims, st, box, es, CU_TENSOR_MAP_INTERLEAVE_NONE, CU_TENSOR_MAP_SWIZZLE_128B,
        CU_TENSOR_MAP_L2_PROMOTION_NONE, CU_TENSOR_MAP_FLOAT_OOB_FILL_NONE);
    return m;
  };
  const CUtensorMap mx = make_map(x, DM, SEQ, 128), mw = make_map(wqkv, 3 * DM, DM, 64);
  const CUtensorMap mo = make_map(wo, DM, DM, 64), m1 = make_map(w1, FF, DM, 64), m2 = make_map(w2, DM, FF, 64);
  launch(k1_qkv, 128, 384, K1_SMEM, 2, false, mx, mw, x, wqkv);
  launch(k2_attn, 132, 512, K2_SMEM, 1, true, mo, m1, m2);
  launch(k3_mlp, 128, 384, K3_SMEM, 2, true, x, b1, b2, (__nv_bfloat16*)d_out);
}
```
